```python
import torch

def _softmax(x, axis=-1):
    return torch.softmax(x, dim=axis)

def _gelu(x):
    return torch.nn.functional.gelu(x, approximate='tanh')

def _silu(x):
    return torch.nn.functional.silu(x)

def _sigmoid(x):
    return torch.sigmoid(x)

def _layernorm(x, axis=-1, eps=1e-05):
    m = x.mean(dim=axis, keepdim=True)
    v = x.var(dim=axis, keepdim=True, unbiased=False)
    return (x - m) / torch.sqrt(v + eps)

def _scatter_add(tgt, idx, src, axis=0):
    return tgt.clone().index_add_(axis, idx, src)

def _segment_sum(src, seg, n):
    out = torch.zeros((n,) + src.shape[1:], dtype=src.dtype)
    return out.index_add_(0, seg, src)

def _pad(x, pw):
    flat = tuple((v for pair in reversed(pw) for v in pair))
    return torch.nn.functional.pad(x, flat)
kernel_name = 'standalone__tree_speculative_verify_tree_attention_over_candidate_token_tree__sampling'

def setup_inputs():

    _w = lambda a: (lambda t: t.to(torch.bfloat16) if t.is_floating_point() else t)(torch.as_tensor(a))
    B, Hq, Hkv, T, C, D = (32, 32, 16, 8, 2048, 128)
    tree_mask = torch.zeros((B, T, T), dtype=float)
    for b in range(B):
        parent = torch.zeros(T, dtype=torch.int64)
        for i in range(1, T):
            parent[i] = int(torch.randint(0, i, (1,)).item())
        for i in range(T):
            j = i
            tree_mask[b, i, j] = 1.0
            while j > 0:
                j = parent[j]
                tree_mask[b, i, j] = 1.0
    return {'q': _w((lambda *s: torch.randn(*s, dtype=torch.bfloat16) * 0.8)(B, Hq, T, D)), 'k_cache': _w((lambda *s: torch.randn(*s, dtype=torch.bfloat16) * 0.8)(B, Hkv, C, D)), 'v_cache': _w((lambda *s: torch.randn(*s, dtype=torch.bfloat16) * 0.05)(B, Hkv, C, D)), 'k_tree': _w((lambda *s: torch.randn(*s, dtype=torch.bfloat16) * 0.8)(B, Hkv, T, D)), 'v_tree': _w((lambda *s: torch.randn(*s, dtype=torch.bfloat16) * 0.05)(B, Hkv, T, D)), 'tree_mask': _w(tree_mask)}

def reference(q, k_cache, v_cache, k_tree, v_tree, tree_mask):
    B, Hq, T, D = q.shape
    Hkv, C = (k_cache.shape[1], k_cache.shape[2])
    rep = Hq // Hkv
    kc = (lambda x, n, axis: torch.repeat_interleave(x, n, dim=axis))(k_cache, rep, axis=1)
    vc = (lambda x, n, axis: torch.repeat_interleave(x, n, dim=axis))(v_cache, rep, axis=1)
    kt = (lambda x, n, axis: torch.repeat_interleave(x, n, dim=axis))(k_tree, rep, axis=1)
    vt = (lambda x, n, axis: torch.repeat_interleave(x, n, dim=axis))(v_tree, rep, axis=1)
    k = torch.concatenate([kc, kt], axis=2)
    v = torch.concatenate([vc, vt], axis=2)
    scale = D ** (-0.5)
    scores = torch.einsum('bhqd,bhkd->bhqk', q, k) * scale
    ctx_mask = torch.ones((B, 1, T, C), dtype=scores.dtype)
    tm = tree_mask[:, None, :, :].clone()
    full_mask = torch.concatenate([ctx_mask, tm], axis=-1)
    scores = scores + (1.0 - full_mask) * -1000000000.0
    p = _softmax(scores, axis=-1)
    return torch.einsum('bhqk,bhkd->bhqd', p, v)
```

```cpp
#include <cuda_runtime.h>
#include <cuda_bf16.h>
#include <cuda.h>
#include <stdint.h>

#define STAGES 6
#define LAYOUT_MODE 1
#define SCHED_MODE 1
#define NCTAS 132

namespace {

constexpr int kB = 32, kHq = 32, kHkv = 16, kT = 8, kC = 2048, kD = 128;
constexpr int kHeads = kB * kHkv;
constexpr int kTile = 64;
constexpr int kTilesPerHead = kC / kTile;
constexpr int kTileBytes = kTile * kD * 2;
constexpr int kTotalTiles = kHeads * kTilesPerHead;
constexpr int kNCW = 4;
constexpr int kThreads = (kNCW + 1) * 32;
constexpr int kAuxBytes = 8192;
constexpr int kRedStride = 136;
constexpr int kMaxParts = 2;

constexpr int kSmemRing = 0;
constexpr int kSmemAux = kSmemRing + STAGES * kTileBytes;
constexpr int kSmemRed = kSmemAux + 2 * kAuxBytes;
constexpr int kSmemML = kSmemRed + kNCW * 16 * kRedStride * 4;
constexpr int kSmemBar = kSmemML + kNCW * 16 * 2 * 4;
constexpr int kSmemTotal = kSmemBar + (2 * STAGES + 4) * 8 + 16;

__device__ float g_part_o[kHeads * kMaxParts * 16 * kD];
__device__ float g_part_ml[kHeads * kMaxParts * 32];
__device__ unsigned g_part_cnt[kHeads];

__device__ __forceinline__ uint32_t smem_u32(const void* p) { return (uint32_t)__cvta_generic_to_shared(p); }
__device__ __forceinline__ void mbar_init(uint32_t bar, int cnt) {
    asm volatile("mbarrier.init.shared::cta.b64 [%0], %1;" ::"r"(bar), "r"(cnt));
}
__device__ __forceinline__ void mbar_expect_tx(uint32_t bar, uint32_t bytes) {
    asm volatile("mbarrier.arrive.expect_tx.shared::cta.b64 _, [%0], %1;" ::"r"(bar), "r"(bytes) : "memory");
}
__device__ __forceinline__ void mbar_arrive(uint32_t bar) {
    asm volatile("mbarrier.arrive.shared::cta.b64 _, [%0];" ::"r"(bar) : "memory");
}
__device__ __forceinline__ bool mbar_try(uint32_t bar, uint32_t parity) {
    uint32_t ok;
    asm volatile(
        "{\n"
        ".reg .pred p;\n"
        "mbarrier.try_wait.parity.shared::cta.b64 p, [%1], %2;\n"
        "selp.u32 %0, 1, 0, p;\n"
        "}\n" : "=r"(ok) : "r"(bar), "r"(parity) : "memory");
    return ok != 0;
}
__device__ __forceinline__ void mbar_wait(uint32_t bar, uint32_t parity) {
    uint32_t spins = 0;
    while (!mbar_try(bar, parity)) {
        if (++spins > (1u << 24)) __trap();
    }
}
__device__ __forceinline__ void bulk_load(uint32_t dst, const void* src, uint32_t bytes, uint32_t bar) {
    asm volatile("cp.async.bulk.shared::cluster.global.mbarrier::complete_tx::bytes [%0], [%1], %2, [%3];"
                 ::"r"(dst), "l"(src), "r"(bytes), "r"(bar) : "memory");
}
__device__ __forceinline__ void tma_load_3d(uint32_t dst, const CUtensorMap* map, int c0, int c1, int c2, uint32_t bar) {
    asm volatile("cp.async.bulk.tensor.3d.shared::cluster.global.mbarrier::complete_tx::bytes [%0], [%1, {%3, %4, %5}], [%2];"
                 ::"r"(dst), "l"((uint64_t)map), "r"(bar), "r"(c0), "r"(c1), "r"(c2) : "memory");
}
__device__ __forceinline__ void ldsm_x4(uint32_t addr, uint32_t& r0, uint32_t& r1, uint32_t& r2, uint32_t& r3) {
    asm volatile("ldmatrix.sync.aligned.m8n8.x4.shared.b16 {%0,%1,%2,%3}, [%4];"
                 : "=r"(r0), "=r"(r1), "=r"(r2), "=r"(r3) : "r"(addr) : "memory");
}
__device__ __forceinline__ void ldsm_x4_t(uint32_t addr, uint32_t& r0, uint32_t& r1, uint32_t& r2, uint32_t& r3) {
    asm volatile("ldmatrix.sync.aligned.m8n8.x4.trans.shared.b16 {%0,%1,%2,%3}, [%4];"
                 : "=r"(r0), "=r"(r1), "=r"(r2), "=r"(r3) : "r"(addr) : "memory");
}
__device__ __forceinline__ void mma_16816(float (&c)[4], const uint32_t (&a)[4], uint32_t b0, uint32_t b1) {
    asm volatile("mma.sync.aligned.m16n8k16.row.col.f32.bf16.bf16.f32 {%0,%1,%2,%3}, {%4,%5,%6,%7}, {%8,%9}, {%0,%1,%2,%3};"
                 : "+f"(c[0]), "+f"(c[1]), "+f"(c[2]), "+f"(c[3])
                 : "r"(a[0]), "r"(a[1]), "r"(a[2]), "r"(a[3]), "r"(b0), "r"(b1));
}
__device__ __forceinline__ void mma_1688(float (&c)[4], uint32_t a0, uint32_t a1, uint32_t b0) {
    asm volatile("mma.sync.aligned.m16n8k8.row.col.f32.bf16.bf16.f32 {%0,%1,%2,%3}, {%4,%5}, {%6}, {%0,%1,%2,%3};"
                 : "+f"(c[0]), "+f"(c[1]), "+f"(c[2]), "+f"(c[3])
                 : "r"(a0), "r"(a1), "r"(b0));
}
__device__ __forceinline__ uint32_t pack_bf16(float lo, float hi) {
    uint32_t r;
    asm("cvt.rn.bf16x2.f32 %0, %1, %2;" : "=r"(r) : "f"(hi), "f"(lo));
    return r;
}
__device__ __forceinline__ float ex2(float x) {
    float y;
    asm("ex2.approx.ftz.f32 %0, %1;" : "=f"(y) : "f"(x));
    return y;
}
__device__ __forceinline__ void consumer_sync() { asm volatile("bar.sync 1, %0;" ::"n"(kNCW * 32) : "memory"); }

__device__ __forceinline__ uint32_t tile_off(int r, int c) {
    return (uint32_t)((c >> 3) * (kTile * 128) + r * 128 + (((c & 7) ^ (r & 7)) << 4));
}

struct Sched {
    int cur, end;
    __device__ __forceinline__ void init(int cta, int ncta) {
        cur = (int)((long long)kTotalTiles * cta / ncta);
        end = (int)((long long)kTotalTiles * (cta + 1) / ncta);
    }
    __device__ __forceinline__ bool next(int& head, int& t0, int& t1) {
        if (cur >= end) return false;
        head = cur / kTilesPerHead;
        t0 = cur - head * kTilesPerHead;
        int e = min(end, (head + 1) * kTilesPerHead);
        t1 = e - head * kTilesPerHead;
        cur = e;
        return true;
    }
};

__global__ void __launch_bounds__(kThreads, 1)
tree_attn_kernel(const __grid_constant__ CUtensorMap map_k, const __grid_constant__ CUtensorMap map_v,
                 const __nv_bfloat16* __restrict__ q, const __nv_bfloat16* __restrict__ k_tree,
                 const __nv_bfloat16* __restrict__ v_tree, const __nv_bfloat16* __restrict__ tree_mask,
                 __nv_bfloat16* __restrict__ out) {
    extern __shared__ __align__(1024) unsigned char smem[];
    const uint32_t sbase = smem_u32(smem);
    const uint32_t bar_full = sbase + kSmemBar;
    const uint32_t bar_empty = bar_full + STAGES * 8;
    const uint32_t bar_afull = bar_empty + STAGES * 8;
    const uint32_t bar_aempty = bar_afull + 16;
    const int warp = threadIdx.x >> 5, lane = threadIdx.x & 31;

    if (threadIdx.x == kNCW * 32) {
        for (int s = 0; s < STAGES; s++) { mbar_init(bar_full + s * 8, 1); mbar_init(bar_empty + s * 8, kNCW); }
        for (int a = 0; a < 2; a++) { mbar_init(bar_afull + a * 8, 1); mbar_init(bar_aempty + a * 8, kNCW); }
        asm volatile("fence.mbarrier_init.release.cluster;" ::: "memory");
    }
    __syncthreads();

    Sched sched;
    sched.init(blockIdx.x, gridDim.x);
    int head, t0, t1;

    if (warp == kNCW) {
        if (lane == 0) {
            int s = 0; uint32_t ph = 1;
            int a = 0; uint32_t aph = 1;
            while (sched.next(head, t0, t1)) {
                bool first = true;
                for (int t = t0; t < t1; t++) {
                    const int row = head * kC + t * kTile;
#pragma unroll
                    for (int kv = 0; kv < 2; kv++) {
                        mbar_wait(bar_empty + s * 8, ph);
                        mbar_expect_tx(bar_full + s * 8, kTileBytes);
                        tma_load_3d(sbase + kSmemRing + s * kTileBytes, kv ? &map_v : &map_k, 0, row, 0, bar_full + s * 8);
                        if (++s == STAGES) { s = 0; ph ^= 1; }
                        if (first) {
                            first = false;
                            mbar_wait(bar_aempty + a * 8, aph);
                            const uint32_t ab = sbase + kSmemAux + a * kAuxBytes;
                            const bool tree = (t0 == 0);
                            mbar_expect_tx(bar_afull + a * 8, tree ? 8192 : 4096);
                            bulk_load(ab, q + (size_t)head * 16 * kD, 4096, bar_afull + a * 8);
                            if (tree) {
                                bulk_load(ab + 4096, k_tree + (size_t)head * kT * kD, 2048, bar_afull + a * 8);
                                bulk_load(ab + 6144, v_tree + (size_t)head * kT * kD, 2048, bar_afull + a * 8);
                            }
                            if (++a == 2) { a = 0; aph ^= 1; }
                        }
                    }
                }
            }
        }
    } else {
        const float kScale = 0.08838834764831845f;
        const float kC2 = kScale * 1.4426950408889634f;
        const int g = lane >> 2, tq = lane & 3;
        int s = 0; uint32_t ph = 0;
        int a = 0; uint32_t aph = 0;
        uint32_t koff[2][4], voff[8];
#pragma unroll
        for (int j = 0; j < 2; j++)
#pragma unroll
            for (int i = 0; i < 4; i++) koff[j][i] = tile_off(16 * warp + 8 * j + (lane & 7), 4 * i + (lane >> 3));
#pragma unroll
        for (int i = 0; i < 8; i++) voff[i] = tile_off(16 * warp + ((lane >> 3) & 1) * 8 + (lane & 7), 2 * i + (lane >> 4));
        float* red = reinterpret_cast<float*>(smem + kSmemRed);
        float* mlbuf = reinterpret_cast<float*>(smem + kSmemML);

        while (sched.next(head, t0, t1)) {
            uint32_t qf[8][4];
            float o[16][4];
            float m0 = -INFINITY, m1 = -INFINITY, l0 = 0.f, l1 = 0.f;
#pragma unroll
            for (int i = 0; i < 16; i++) { o[i][0] = 0.f; o[i][1] = 0.f; o[i][2] = 0.f; o[i][3] = 0.f; }
            const bool tree = (t0 == 0) && (warp == 0);
            uint32_t mraw = 0;
            if (tree) mraw = __ldg(reinterpret_cast<const uint32_t*>(tree_mask + (head / kHkv) * kT * kT + g * kT + 2 * tq));

            const uint32_t ab = sbase + kSmemAux + a * kAuxBytes;
            mbar_wait(bar_afull + a * 8, aph);
#pragma unroll
            for (int ks = 0; ks < 8; ks++)
                ldsm_x4(ab + ((lane & 7) + ((lane >> 3) & 1) * 8) * 256 + (2 * ks + (lane >> 4)) * 16,
                        qf[ks][0], qf[ks][1], qf[ks][2], qf[ks][3]);
            if (tree) {
                float sc[4] = {0.f, 0.f, 0.f, 0.f};
#pragma unroll
                for (int i = 0; i < 4; i++) {
                    uint32_t b0, b1, b2, b3;
                    ldsm_x4(ab + 4096 + (lane & 7) * 256 + (4 * i + (lane >> 3)) * 16, b0, b1, b2, b3);
                    mma_16816(sc, qf[2 * i], b0, b1);
                    mma_16816(sc, qf[2 * i + 1], b2, b3);
                }
                const float mk0 = __uint_as_float(mraw << 16), mk1 = __uint_as_float(mraw & 0xffff0000u);
                const float bias0 = (1.0f - mk0) * (-1000000000.0f / kScale);
                const float bias1 = (1.0f - mk1) * (-1000000000.0f / kScale);
                sc[0] += bias0; sc[1] += bias1; sc[2] += bias0; sc[3] += bias1;
                float mx0 = fmaxf(sc[0], sc[1]), mx1 = fmaxf(sc[2], sc[3]);
                mx0 = fmaxf(mx0, __shfl_xor_sync(0xffffffffu, mx0, 1));
                mx1 = fmaxf(mx1, __shfl_xor_sync(0xffffffffu, mx1, 1));
                mx0 = fmaxf(mx0, __shfl_xor_sync(0xffffffffu, mx0, 2));
                mx1 = fmaxf(mx1, __shfl_xor_sync(0xffffffffu, mx1, 2));
                m0 = mx0; m1 = mx1;
                const float p0 = ex2((sc[0] - m0) * kC2), p1 = ex2((sc[1] - m0) * kC2);
                const float p2 = ex2((sc[2] - m1) * kC2), p3 = ex2((sc[3] - m1) * kC2);
                l0 = p0 + p1; l1 = p2 + p3;
                const uint32_t pa0 = pack_bf16(p0, p1), pa1 = pack_bf16(p2, p3);
#pragma unroll
                for (int i = 0; i < 4; i++) {
                    uint32_t b0, b1, b2, b3;
                    ldsm_x4_t(ab + 6144 + (lane & 7) * 256 + (4 * i + (lane >> 3)) * 16, b0, b1, b2, b3);
                    mma_1688(o[4 * i + 0], pa0, pa1, b0);
                    mma_1688(o[4 * i + 1], pa0, pa1, b1);
                    mma_1688(o[4 * i + 2], pa0, pa1, b2);
                    mma_1688(o[4 * i + 3], pa0, pa1, b3);
                }
            }
            __syncwarp();
            if (lane == 0) mbar_arrive(bar_aempty + a * 8);
            if (++a == 2) { a = 0; aph ^= 1; }

            for (int t = t0; t < t1; t++) {
                float sc[2][4];
#pragma unroll
                for (int j = 0; j < 2; j++) { sc[j][0] = 0.f; sc[j][1] = 0.f; sc[j][2] = 0.f; sc[j][3] = 0.f; }
                {
                    const uint32_t kb = sbase + kSmemRing + s * kTileBytes;
                    mbar_wait(bar_full + s * 8, ph);
#pragma unroll
                    for (int i = 0; i < 4; i++) {
#pragma unroll
                        for (int j = 0; j < 2; j++) {
                            uint32_t b0, b1, b2, b3;
                            ldsm_x4(kb + koff[j][i], b0, b1, b2, b3);
                            mma_16816(sc[j], qf[2 * i], b0, b1);
                            mma_16816(sc[j], qf[2 * i + 1], b2, b3);
                        }
                    }
                    __syncwarp();
                    if (lane == 0) mbar_arrive(bar_empty + s * 8);
                    if (++s == STAGES) { s = 0; ph ^= 1; }
                }
                float mx0 = fmaxf(fmaxf(sc[0][0], sc[0][1]), fmaxf(sc[1][0], sc[1][1]));
                float mx1 = fmaxf(fmaxf(sc[0][2], sc[0][3]), fmaxf(sc[1][2], sc[1][3]));
                mx0 = fmaxf(mx0, __shfl_xor_sync(0xffffffffu, mx0, 1));
                mx1 = fmaxf(mx1, __shfl_xor_sync(0xffffffffu, mx1, 1));
                mx0 = fmaxf(mx0, __shfl_xor_sync(0xffffffffu, mx0, 2));
                mx1 = fmaxf(mx1, __shfl_xor_sync(0xffffffffu, mx1, 2));
                const float mn0 = fmaxf(m0, mx0), mn1 = fmaxf(m1, mx1);
                const float al0 = ex2((m0 - mn0) * kC2), al1 = ex2((m1 - mn1) * kC2);
                m0 = mn0; m1 = mn1;
                const float mb0 = mn0 * kC2, mb1 = mn1 * kC2;
                uint32_t pa[4];
                {
                    const float p00 = ex2(fmaf(sc[0][0], kC2, -mb0)), p01 = ex2(fmaf(sc[0][1], kC2, -mb0));
                    const float p02 = ex2(fmaf(sc[0][2], kC2, -mb1)), p03 = ex2(fmaf(sc[0][3], kC2, -mb1));
                    const float p10 = ex2(fmaf(sc[1][0], kC2, -mb0)), p11 = ex2(fmaf(sc[1][1], kC2, -mb0));
                    const float p12 = ex2(fmaf(sc[1][2], kC2, -mb1)), p13 = ex2(fmaf(sc[1][3], kC2, -mb1));
                    l0 = fmaf(l0, al0, (p00 + p01) + (p10 + p11));
                    l1 = fmaf(l1, al1, (p02 + p03) + (p12 + p13));
                    pa[0] = pack_bf16(p00, p01); pa[1] = pack_bf16(p02, p03);
                    pa[2] = pack_bf16(p10, p11); pa[3] = pack_bf16(p12, p13);
                }
#pragma unroll
                for (int i = 0; i < 16; i++) { o[i][0] *= al0; o[i][1] *= al0; o[i][2] *= al1; o[i][3] *= al1; }
                {
                    const uint32_t vb = sbase + kSmemRing + s * kTileBytes;
                    mbar_wait(bar_full + s * 8, ph);
#pragma unroll
                    for (int i = 0; i < 8; i++) {
                        uint32_t b0, b1, b2, b3;
                        ldsm_x4_t(vb + voff[i], b0, b1, b2, b3);
                        mma_16816(o[2 * i], pa, b0, b1);
                        mma_16816(o[2 * i + 1], pa, b2, b3);
                    }
                    __syncwarp();
                    if (lane == 0) mbar_arrive(bar_empty + s * 8);
                    if (++s == STAGES) { s = 0; ph ^= 1; }
                }
            }

            l0 += __shfl_xor_sync(0xffffffffu, l0, 1);
            l1 += __shfl_xor_sync(0xffffffffu, l1, 1);
            l0 += __shfl_xor_sync(0xffffffffu, l0, 2);
            l1 += __shfl_xor_sync(0xffffffffu, l1, 2);
            if (tq == 0) {
                mlbuf[(warp * 16 + g) * 2] = m0; mlbuf[(warp * 16 + g) * 2 + 1] = l0;
                mlbuf[(warp * 16 + g + 8) * 2] = m1; mlbuf[(warp * 16 + g + 8) * 2 + 1] = l1;
            }
            consumer_sync();
            {
                float M0 = m0, M1 = m1;
#pragma unroll
                for (int w = 0; w < kNCW; w++) {
                    M0 = fmaxf(M0, mlbuf[(w * 16 + g) * 2]);
                    M1 = fmaxf(M1, mlbuf[(w * 16 + g + 8) * 2]);
                }
                const float f0 = ex2((m0 - M0) * kC2), f1 = ex2((m1 - M1) * kC2);
                float* r0 = red + (warp * 16 + g) * kRedStride + 2 * tq;
                float* r1 = r0 + 8 * kRedStride;
#pragma unroll
                for (int i = 0; i < 16; i++) {
                    *reinterpret_cast<float2*>(r0 + 8 * i) = make_float2(o[i][0] * f0, o[i][1] * f0);
                    *reinterpret_cast<float2*>(r1 + 8 * i) = make_float2(o[i][2] * f1, o[i][3] * f1);
                }
            }
            const int row = threadIdx.x >> 3, c8 = threadIdx.x & 7;
            float M = -INFINITY, L = 0.f;
#pragma unroll
            for (int w = 0; w < kNCW; w++) M = fmaxf(M, mlbuf[(w * 16 + row) * 2]);
#pragma unroll
            for (int w = 0; w < kNCW; w++) L += mlbuf[(w * 16 + row) * 2 + 1] * ex2((mlbuf[(w * 16 + row) * 2] - M) * kC2);
            consumer_sync();
            float4 acc[4];
#pragma unroll
            for (int i = 0; i < 4; i++) {
                acc[i] = *reinterpret_cast<const float4*>(red + row * kRedStride + 32 * i + 4 * c8);
#pragma unroll
                for (int w = 1; w < kNCW; w++) {
                    const float4 v = *reinterpret_cast<const float4*>(red + (w * 16 + row) * kRedStride + 32 * i + 4 * c8);
                    acc[i].x += v.x; acc[i].y += v.y; acc[i].z += v.z; acc[i].w += v.w;
                }
            }
            bool write_out = true;
            if (t1 - t0 != kTilesPerHead) {
                const int part = (t0 == 0) ? 0 : 1;
                float* po = g_part_o + ((size_t)(head * kMaxParts + part) * 16 + row) * kD;
#pragma unroll
                for (int i = 0; i < 4; i++) __stcg(reinterpret_cast<float4*>(po + 32 * i + 4 * c8), acc[i]);
                if (c8 == 0) __stcg(reinterpret_cast<float2*>(g_part_ml + (head * kMaxParts + part) * 32 + row * 2), make_float2(M, L));
                __threadfence();
                consumer_sync();
                if (threadIdx.x == 0) {
                    const unsigned old = atomicAdd(&g_part_cnt[head], 1u);
                    if (old == kMaxParts - 1) g_part_cnt[head] = 0;
                    mlbuf[0] = __uint_as_float(old);
                }
                consumer_sync();
                write_out = (__float_as_uint(mlbuf[0]) == kMaxParts - 1);
                if (write_out) {
                    __threadfence();
                    const int op = part ^ 1;
                    const float2 ml = __ldcg(reinterpret_cast<const float2*>(g_part_ml + (head * kMaxParts + op) * 32 + row * 2));
                    const float Mn = fmaxf(M, ml.x);
                    const float fa = ex2((M - Mn) * kC2), fb = ex2((ml.x - Mn) * kC2);
                    L = L * fa + ml.y * fb;
                    const float* qo = g_part_o + ((size_t)(head * kMaxParts + op) * 16 + row) * kD;
#pragma unroll
                    for (int i = 0; i < 4; i++) {
                        const float4 v = __ldcg(reinterpret_cast<const float4*>(qo + 32 * i + 4 * c8));
                        acc[i].x = acc[i].x * fa + v.x * fb; acc[i].y = acc[i].y * fa + v.y * fb;
                        acc[i].z = acc[i].z * fa + v.z * fb; acc[i].w = acc[i].w * fa + v.w * fb;
                    }
                }
            }
            if (write_out) {
                const float inv = 1.0f / L;
                __nv_bfloat16* op = out + ((size_t)head * 16 + row) * kD;
#pragma unroll
                for (int i = 0; i < 4; i++) {
                    uint2 v;
                    v.x = pack_bf16(acc[i].x * inv, acc[i].y * inv);
                    v.y = pack_bf16(acc[i].z * inv, acc[i].w * inv);
                    *reinterpret_cast<uint2*>(op + 32 * i + 4 * c8) = v;
                }
            }
            consumer_sync();
        }
    }
}

typedef CUresult (*EncodeTiledFn)(CUtensorMap*, CUtensorMapDataType, cuuint32_t, void*, const cuuint64_t*, const cuuint64_t*,
                                  const cuuint32_t*, const cuuint32_t*, CUtensorMapInterleave, CUtensorMapSwizzle,
                                  CUtensorMapL2promotion, CUtensorMapFloatOOBfill);

void make_map(EncodeTiledFn enc, CUtensorMap* map, const void* ptr) {
    const cuuint64_t rows = (cuuint64_t)kHeads * kC;
    cuuint64_t dims[3] = {64, rows, 2};
    cuuint64_t strides[2] = {256, 128};
    cuuint32_t box[3] = {64, (cuuint32_t)kTile, 2};
    cuuint32_t estr[3] = {1, 1, 1};
    enc(map, CU_TENSOR_MAP_DATA_TYPE_BFLOAT16, 3, const_cast<void*>(ptr), dims, strides, box, estr,
        CU_TENSOR_MAP_INTERLEAVE_NONE, CU_TENSOR_MAP_SWIZZLE_128B, CU_TENSOR_MAP_L2_PROMOTION_L2_128B,
        CU_TENSOR_MAP_FLOAT_OOB_FILL_NONE);
}

}

extern "C" void kernel_launch(void* const* d_in, const int* in_sizes, int n_in, void* d_out, int out_size) {
    (void)in_sizes; (void)n_in; (void)out_size;
    static EncodeTiledFn enc = nullptr;
    if (!enc) {
        void* fn = nullptr;
        cudaDriverEntryPointQueryResult qres;
        cudaGetDriverEntryPoint("cuTensorMapEncodeTiled", &fn, cudaEnableDefault, &qres);
        enc = (EncodeTiledFn)fn;
        cudaFuncSetAttribute(tree_attn_kernel, cudaFuncAttributeMaxDynamicSharedMemorySize, kSmemTotal);
    }
    CUtensorMap map_k, map_v;
    make_map(enc, &map_k, d_in[1]);
    make_map(enc, &map_v, d_in[2]);
    tree_attn_kernel<<<NCTAS, kThreads, kSmemTotal>>>(
        map_k, map_v, (const __nv_bfloat16*)d_in[0], (const __nv_bfloat16*)d_in[3], (const __nv_bfloat16*)d_in[4],
        (const __nv_bfloat16*)d_in[5], (__nv_bfloat16*)d_out);
}
```

```cpp
#include <cuda_runtime.h>
#include <cuda_bf16.h>
#include <cuda.h>
#include <stdint.h>

#define STAGES 8
#define INFLIGHT 4
#define OUT_MODE 0
#define FLUSH_AT 240
#define EVICT_FIRST 1
#define L2PROMO CU_TENSOR_MAP_L2_PROMOTION_L2_128B

namespace {

constexpr int kB = 32, kHkv = 16, kT = 8, kC = 2048, kD = 128;
constexpr int kHeads = kB * kHkv;
constexpr int kCtas = 128;
constexpr int kRounds = kHeads / kCtas;
constexpr int kTile = 64;
constexpr int kTilesPerHead = kC / kTile;
constexpr int kTileBytes = kTile * kD * 2;
constexpr int kLoads = kRounds * kTilesPerHead * 2;
constexpr int kNCW = 4;
constexpr int kThreads = (kNCW + 1) * 32;
constexpr int kAuxBytes = 8192;
constexpr int kRedStride = 136;

constexpr int kSmemRing = 0;
constexpr int kSmemAux = kSmemRing + STAGES * kTileBytes;
constexpr int kSmemRed = kSmemAux + kRounds * kAuxBytes;
constexpr int kSmemML = kSmemRed + kNCW * 16 * kRedStride * 4;
constexpr int kSmemBar = kSmemML + kNCW * 16 * 2 * 4;
constexpr int kSmemTotal = kSmemBar + (2 * STAGES + kRounds) * 8;

#define TS(i)

__device__ __forceinline__ uint32_t smem_u32(const void* p) { return (uint32_t)__cvta_generic_to_shared(p); }
__device__ __forceinline__ void mbar_init(uint32_t bar, int cnt) {
    asm volatile("mbarrier.init.shared::cta.b64 [%0], %1;" ::"r"(bar), "r"(cnt));
}
__device__ __forceinline__ void mbar_expect_tx(uint32_t bar, uint32_t bytes) {
    asm volatile("mbarrier.arrive.expect_tx.shared::cta.b64 _, [%0], %1;" ::"r"(bar), "r"(bytes) : "memory");
}
__device__ __forceinline__ void mbar_arrive(uint32_t bar) {
    asm volatile("mbarrier.arrive.shared::cta.b64 _, [%0];" ::"r"(bar) : "memory");
}
__device__ __forceinline__ bool mbar_try(uint32_t bar, uint32_t parity) {
    uint32_t ok;
    asm volatile(
        "{\n"
        ".reg .pred p;\n"
        "mbarrier.try_wait.parity.shared::cta.b64 p, [%1], %2;\n"
        "selp.u32 %0, 1, 0, p;\n"
        "}\n" : "=r"(ok) : "r"(bar), "r"(parity) : "memory");
    return ok != 0;
}
__device__ __forceinline__ void mbar_wait(uint32_t bar, uint32_t parity) {
    uint32_t spins = 0;
    while (!mbar_try(bar, parity)) {
        if (++spins > (1u << 24)) __trap();
    }
}
__device__ __forceinline__ void bulk_load(uint32_t dst, const void* src, uint32_t bytes, uint32_t bar) {
    asm volatile("cp.async.bulk.shared::cluster.global.mbarrier::complete_tx::bytes [%0], [%1], %2, [%3];"
                 ::"r"(dst), "l"(src), "r"(bytes), "r"(bar) : "memory");
}
__device__ __forceinline__ void bulk_store(void* dst, uint32_t src, uint32_t bytes) {
    asm volatile("cp.async.bulk.global.shared::cta.bulk_group [%0], [%1], %2;" ::"l"(dst), "r"(src), "r"(bytes) : "memory");
}
__device__ __forceinline__ void tma_load_3d(uint32_t dst, const CUtensorMap* map, int c1, uint32_t bar, uint64_t pol) {
    asm volatile("cp.async.bulk.tensor.3d.shared::cluster.global.mbarrier::complete_tx::bytes.L2::cache_hint [%0], [%1, {%3, %4, %3}], [%2], %5;"
                 ::"r"(dst), "l"((uint64_t)map), "r"(bar), "r"(0), "r"(c1), "l"(pol) : "memory");
}
__device__ __forceinline__ void ldsm_x4(uint32_t addr, uint32_t& r0, uint32_t& r1, uint32_t& r2, uint32_t& r3) {
    asm volatile("ldmatrix.sync.aligned.m8n8.x4.shared.b16 {%0,%1,%2,%3}, [%4];"
                 : "=r"(r0), "=r"(r1), "=r"(r2), "=r"(r3) : "r"(addr) : "memory");
}
__device__ __forceinline__ void ldsm_x4_t(uint32_t addr, uint32_t& r0, uint32_t& r1, uint32_t& r2, uint32_t& r3) {
    asm volatile("ldmatrix.sync.aligned.m8n8.x4.trans.shared.b16 {%0,%1,%2,%3}, [%4];"
                 : "=r"(r0), "=r"(r1), "=r"(r2), "=r"(r3) : "r"(addr) : "memory");
}
__device__ __forceinline__ void mma_16816(float (&c)[4], const uint32_t (&a)[4], uint32_t b0, uint32_t b1) {
    asm volatile("mma.sync.aligned.m16n8k16.row.col.f32.bf16.bf16.f32 {%0,%1,%2,%3}, {%4,%5,%6,%7}, {%8,%9}, {%0,%1,%2,%3};"
                 : "+f"(c[0]), "+f"(c[1]), "+f"(c[2]), "+f"(c[3])
                 : "r"(a[0]), "r"(a[1]), "r"(a[2]), "r"(a[3]), "r"(b0), "r"(b1));
}
__device__ __forceinline__ void mma_1688(float (&c)[4], uint32_t a0, uint32_t a1, uint32_t b0) {
    asm volatile("mma.sync.aligned.m16n8k8.row.col.f32.bf16.bf16.f32 {%0,%1,%2,%3}, {%4,%5}, {%6}, {%0,%1,%2,%3};"
                 : "+f"(c[0]), "+f"(c[1]), "+f"(c[2]), "+f"(c[3])
                 : "r"(a0), "r"(a1), "r"(b0));
}
__device__ __forceinline__ uint32_t pack_bf16(float lo, float hi) {
    uint32_t r;
    asm("cvt.rn.bf16x2.f32 %0, %1, %2;" : "=r"(r) : "f"(hi), "f"(lo));
    return r;
}
__device__ __forceinline__ float ex2(float x) {
    float y;
    asm("ex2.approx.ftz.f32 %0, %1;" : "=f"(y) : "f"(x));
    return y;
}
__device__ __forceinline__ void consumer_sync() { asm volatile("bar.sync 1, %0;" ::"n"(kNCW * 32) : "memory"); }

__device__ __forceinline__ uint32_t tile_off(int r, int c) {
    return (uint32_t)((c >> 3) * (kTile * 128) + r * 128 + (((c & 7) ^ (r & 7)) << 4));
}

__global__ void __launch_bounds__(kThreads, 1)
tree_attn_kernel(const __grid_constant__ CUtensorMap map_k, const __grid_constant__ CUtensorMap map_v,
                 const __nv_bfloat16* __restrict__ q, const __nv_bfloat16* __restrict__ k_tree,
                 const __nv_bfloat16* __restrict__ v_tree, const __nv_bfloat16* __restrict__ tree_mask,
                 __nv_bfloat16* __restrict__ out) {
    extern __shared__ __align__(1024) unsigned char smem[];
    const uint32_t sbase = smem_u32(smem);
    const uint32_t bar_full = sbase + kSmemBar;
    const uint32_t bar_empty = bar_full + STAGES * 8;
    const uint32_t bar_aux = bar_empty + STAGES * 8;
    const int warp = threadIdx.x >> 5, lane = threadIdx.x & 31;
    const int cta = blockIdx.x;

    uint64_t pol = 0;
    auto issue_aux = [&](int r) {
        const int head = cta + r * kCtas;
        const uint32_t ab = sbase + kSmemAux + r * kAuxBytes;
        mbar_expect_tx(bar_aux + r * 8, kAuxBytes);
        bulk_load(ab, q + (size_t)head * 16 * kD, 4096, bar_aux + r * 8);
        bulk_load(ab + 4096, k_tree + (size_t)head * kT * kD, 2048, bar_aux + r * 8);
        bulk_load(ab + 6144, v_tree + (size_t)head * kT * kD, 2048, bar_aux + r * 8);
    };

    if (threadIdx.x == kNCW * 32) {
        TS(0);
        asm volatile("createpolicy.fractional.L2::evict_first.b64 %0, 1.0;" : "=l"(pol));
#pragma unroll
        for (int s = 0; s < STAGES; s++) mbar_init(bar_full + s * 8, 1);
        asm volatile("fence.mbarrier_init.release.cluster;" ::: "memory");
#pragma unroll
        for (int i = 0; i < INFLIGHT; i++) {
            mbar_expect_tx(bar_full + i * 8, kTileBytes);
            tma_load_3d(sbase + kSmemRing + i * kTileBytes, (i & 1) ? &map_v : &map_k, cta * kC + (i >> 1) * kTile, bar_full + i * 8, pol);
        }
        TS(1);
#pragma unroll
        for (int s = 0; s < STAGES; s++) mbar_init(bar_empty + s * 8, kNCW);
#pragma unroll
        for (int r = 0; r < kRounds; r++) mbar_init(bar_aux + r * 8, 1);
        asm volatile("fence.mbarrier_init.release.cluster;" ::: "memory");
        issue_aux(0);
    }
    __syncthreads();

    if (warp == kNCW) {
        if (lane == 0) {
            int s = INFLIGHT % STAGES; uint32_t ph = (INFLIGHT == STAGES) ? 0 : 1;
            int ls = 0; uint32_t lph = 0;
            for (int i = INFLIGHT; i < kLoads; i++) {
                const int row = (cta + (i >> 6) * kCtas) * kC + ((i >> 1) & 31) * kTile;
                if (INFLIGHT < STAGES) {
                    mbar_wait(bar_full + ls * 8, lph);
                    if (++ls == STAGES) { ls = 0; lph ^= 1; }
                }
                mbar_wait(bar_empty + s * 8, ph);
                mbar_expect_tx(bar_full + s * 8, kTileBytes);
                tma_load_3d(sbase + kSmemRing + s * kTileBytes, (i & 1) ? &map_v : &map_k, row, bar_full + s * 8, pol);
                if (++s == STAGES) { s = 0; ph ^= 1; }
                if ((i & 63) == 40 && i < kLoads - 64) issue_aux((i >> 6) + 1);
            }
        }
    } else {
        const float kScale = 0.08838834764831845f;
        const float kC2 = kScale * 1.4426950408889634f;
        const int g = lane >> 2, tq = lane & 3;
        int s = 0; uint32_t ph = 0;
        uint32_t koff[2][4], voff[8];
#pragma unroll
        for (int j = 0; j < 2; j++)
#pragma unroll
            for (int i = 0; i < 4; i++) koff[j][i] = tile_off(16 * warp + 8 * j + (lane & 7), 4 * i + (lane >> 3));
#pragma unroll
        for (int i = 0; i < 8; i++) voff[i] = tile_off(16 * warp + ((lane >> 3) & 1) * 8 + (lane & 7), 2 * i + (lane >> 4));
        float* red = reinterpret_cast<float*>(smem + kSmemRed);
        float* mlbuf = reinterpret_cast<float*>(smem + kSmemML);

#pragma unroll 1
        for (int r = 0; r < kRounds; r++) {
            const int head = cta + r * kCtas;
            uint32_t qf[8][4];
            float o[16][4];
            float m0 = -INFINITY, m1 = -INFINITY, l0 = 0.f, l1 = 0.f;
#pragma unroll
            for (int i = 0; i < 16; i++) { o[i][0] = 0.f; o[i][1] = 0.f; o[i][2] = 0.f; o[i][3] = 0.f; }
            uint32_t mraw = 0;
            if (warp == 0) mraw = __ldg(reinterpret_cast<const uint32_t*>(tree_mask + (head / kHkv) * kT * kT + g * kT + 2 * tq));

            const uint32_t ab = sbase + kSmemAux + r * kAuxBytes;
            mbar_wait(bar_aux + r * 8, 0);
#pragma unroll
            for (int ks = 0; ks < 8; ks++)
                ldsm_x4(ab + ((lane & 7) + ((lane >> 3) & 1) * 8) * 256 + (2 * ks + (lane >> 4)) * 16,
                        qf[ks][0], qf[ks][1], qf[ks][2], qf[ks][3]);
            if (warp == 0) {
                float sc[4] = {0.f, 0.f, 0.f, 0.f};
#pragma unroll
                for (int i = 0; i < 4; i++) {
                    uint32_t b0, b1, b2, b3;
                    ldsm_x4(ab + 4096 + (lane & 7) * 256 + (4 * i + (lane >> 3)) * 16, b0, b1, b2, b3);
                    mma_16816(sc, qf[2 * i], b0, b1);
                    mma_16816(sc, qf[2 * i + 1], b2, b3);
                }
                const float mk0 = __uint_as_float(mraw << 16), mk1 = __uint_as_float(mraw & 0xffff0000u);
                const float bias0 = (1.0f - mk0) * (-1000000000.0f / kScale);
                const float bias1 = (1.0f - mk1) * (-1000000000.0f / kScale);
                sc[0] += bias0; sc[1] += bias1; sc[2] += bias0; sc[3] += bias1;
                float mx0 = fmaxf(sc[0], sc[1]), mx1 = fmaxf(sc[2], sc[3]);
                mx0 = fmaxf(mx0, __shfl_xor_sync(0xffffffffu, mx0, 1));
                mx1 = fmaxf(mx1, __shfl_xor_sync(0xffffffffu, mx1, 1));
                mx0 = fmaxf(mx0, __shfl_xor_sync(0xffffffffu, mx0, 2));
                mx1 = fmaxf(mx1, __shfl_xor_sync(0xffffffffu, mx1, 2));
                m0 = mx0; m1 = mx1;
                const float p0 = ex2((sc[0] - m0) * kC2), p1 = ex2((sc[1] - m0) * kC2);
                const float p2 = ex2((sc[2] - m1) * kC2), p3 = ex2((sc[3] - m1) * kC2);
                l0 = p0 + p1; l1 = p2 + p3;
                const uint32_t pa0 = pack_bf16(p0, p1), pa1 = pack_bf16(p2, p3);
#pragma unroll
                for (int i = 0; i < 4; i++) {
                    uint32_t b0, b1, b2, b3;
                    ldsm_x4_t(ab + 6144 + (lane & 7) * 256 + (4 * i + (lane >> 3)) * 16, b0, b1, b2, b3);
                    mma_1688(o[4 * i + 0], pa0, pa1, b0);
                    mma_1688(o[4 * i + 1], pa0, pa1, b1);
                    mma_1688(o[4 * i + 2], pa0, pa1, b2);
                    mma_1688(o[4 * i + 3], pa0, pa1, b3);
                }
            }

#pragma unroll 1
            for (int t = 0; t < kTilesPerHead; t++) {
                float sc[2][4];
#pragma unroll
                for (int j = 0; j < 2; j++) { sc[j][0] = 0.f; sc[j][1] = 0.f; sc[j][2] = 0.f; sc[j][3] = 0.f; }
                {
                    const uint32_t kb = sbase + kSmemRing + s * kTileBytes;
                    mbar_wait(bar_full + s * 8, ph);
                    if (threadIdx.x == 0 && r == 0 && t == 0) TS(2);
#pragma unroll
                    for (int i = 0; i < 4; i++) {
#pragma unroll
                        for (int j = 0; j < 2; j++) {
                            uint32_t b0, b1, b2, b3;
                            ldsm_x4(kb + koff[j][i], b0, b1, b2, b3);
                            mma_16816(sc[j], qf[2 * i], b0, b1);
                            mma_16816(sc[j], qf[2 * i + 1], b2, b3);
                        }
                    }
                    __syncwarp();
                    if (lane == 0) mbar_arrive(bar_empty + s * 8);
                    if (++s == STAGES) { s = 0; ph ^= 1; }
                }
                float mx0 = fmaxf(fmaxf(sc[0][0], sc[0][1]), fmaxf(sc[1][0], sc[1][1]));
                float mx1 = fmaxf(fmaxf(sc[0][2], sc[0][3]), fmaxf(sc[1][2], sc[1][3]));
                mx0 = fmaxf(mx0, __shfl_xor_sync(0xffffffffu, mx0, 1));
                mx1 = fmaxf(mx1, __shfl_xor_sync(0xffffffffu, mx1, 1));
                mx0 = fmaxf(mx0, __shfl_xor_sync(0xffffffffu, mx0, 2));
                mx1 = fmaxf(mx1, __shfl_xor_sync(0xffffffffu, mx1, 2));
                const float mn0 = fmaxf(m0, mx0), mn1 = fmaxf(m1, mx1);
                const float al0 = ex2((m0 - mn0) * kC2), al1 = ex2((m1 - mn1) * kC2);
                m0 = mn0; m1 = mn1;
                const float mb0 = mn0 * kC2, mb1 = mn1 * kC2;
                uint32_t pa[4];
                {
                    const float p00 = ex2(fmaf(sc[0][0], kC2, -mb0)), p01 = ex2(fmaf(sc[0][1], kC2, -mb0));
                    const float p02 = ex2(fmaf(sc[0][2], kC2, -mb1)), p03 = ex2(fmaf(sc[0][3], kC2, -mb1));
                    const float p10 = ex2(fmaf(sc[1][0], kC2, -mb0)), p11 = ex2(fmaf(sc[1][1], kC2, -mb0));
                    const float p12 = ex2(fmaf(sc[1][2], kC2, -mb1)), p13 = ex2(fmaf(sc[1][3], kC2, -mb1));
                    l0 = fmaf(l0, al0, (p00 + p01) + (p10 + p11));
                    l1 = fmaf(l1, al1, (p02 + p03) + (p12 + p13));
                    pa[0] = pack_bf16(p00, p01); pa[1] = pack_bf16(p02, p03);
                    pa[2] = pack_bf16(p10, p11); pa[3] = pack_bf16(p12, p13);
                }
#pragma unroll
                for (int i = 0; i < 16; i++) { o[i][0] *= al0; o[i][1] *= al0; o[i][2] *= al1; o[i][3] *= al1; }
                {
                    const uint32_t vb = sbase + kSmemRing + s * kTileBytes;
                    mbar_wait(bar_full + s * 8, ph);
                    if (threadIdx.x == 0 && t == kTilesPerHead - 1) TS(3);
#pragma unroll
                    for (int i = 0; i < 8; i++) {
                        uint32_t b0, b1, b2, b3;
                        ldsm_x4_t(vb + voff[i], b0, b1, b2, b3);
                        mma_16816(o[2 * i], pa, b0, b1);
                        mma_16816(o[2 * i + 1], pa, b2, b3);
                    }
                    __syncwarp();
                    if (lane == 0) mbar_arrive(bar_empty + s * 8);
                    if (++s == STAGES) { s = 0; ph ^= 1; }
                }
            }

            l0 += __shfl_xor_sync(0xffffffffu, l0, 1);
            l1 += __shfl_xor_sync(0xffffffffu, l1, 1);
            l0 += __shfl_xor_sync(0xffffffffu, l0, 2);
            l1 += __shfl_xor_sync(0xffffffffu, l1, 2);
            if (tq == 0) {
                mlbuf[(warp * 16 + g) * 2] = m0; mlbuf[(warp * 16 + g) * 2 + 1] = l0;
                mlbuf[(warp * 16 + g + 8) * 2] = m1; mlbuf[(warp * 16 + g + 8) * 2 + 1] = l1;
            }
            consumer_sync();
            {
                float M0 = m0, M1 = m1;
#pragma unroll
                for (int w = 0; w < kNCW; w++) {
                    M0 = fmaxf(M0, mlbuf[(w * 16 + g) * 2]);
                    M1 = fmaxf(M1, mlbuf[(w * 16 + g + 8) * 2]);
                }
                const float f0 = ex2((m0 - M0) * kC2), f1 = ex2((m1 - M1) * kC2);
                float* r0 = red + (warp * 16 + g) * kRedStride + 2 * tq;
                float* r1 = r0 + 8 * kRedStride;
#pragma unroll
                for (int i = 0; i < 16; i++) {
                    *reinterpret_cast<float2*>(r0 + 8 * i) = make_float2(o[i][0] * f0, o[i][1] * f0);
                    *reinterpret_cast<float2*>(r1 + 8 * i) = make_float2(o[i][2] * f1, o[i][3] * f1);
                }
            }
            const int row = threadIdx.x >> 3, c8 = threadIdx.x & 7;
            float M = -INFINITY, L = 0.f;
#pragma unroll
            for (int w = 0; w < kNCW; w++) M = fmaxf(M, mlbuf[(w * 16 + row) * 2]);
#pragma unroll
            for (int w = 0; w < kNCW; w++) L += mlbuf[(w * 16 + row) * 2 + 1] * ex2((mlbuf[(w * 16 + row) * 2] - M) * kC2);
            const float inv = 1.0f / L;
            consumer_sync();
            {
                __nv_bfloat16* op = out + ((size_t)head * 16 + row) * kD;
#pragma unroll
                for (int i = 0; i < 4; i++) {
                    float4 acc = *reinterpret_cast<const float4*>(red + row * kRedStride + 32 * i + 4 * c8);
#pragma unroll
                    for (int w = 1; w < kNCW; w++) {
                        const float4 v = *reinterpret_cast<const float4*>(red + (w * 16 + row) * kRedStride + 32 * i + 4 * c8);
                        acc.x += v.x; acc.y += v.y; acc.z += v.z; acc.w += v.w;
                    }
                    uint2 v;
                    v.x = pack_bf16(acc.x * inv, acc.y * inv);
                    v.y = pack_bf16(acc.z * inv, acc.w * inv);
                    *reinterpret_cast<uint2*>(op + 32 * i + 4 * c8) = v;
                }
            }
            consumer_sync();
            if (threadIdx.x == 0) TS(4);
        }
    }
}

typedef CUresult (*EncodeTiledFn)(CUtensorMap*, CUtensorMapDataType, cuuint32_t, void*, const cuuint64_t*, const cuuint64_t*,
                                  const cuuint32_t*, const cuuint32_t*, CUtensorMapInterleave, CUtensorMapSwizzle,
                                  CUtensorMapL2promotion, CUtensorMapFloatOOBfill);

void make_map(EncodeTiledFn enc, CUtensorMap* map, const void* ptr) {
    const cuuint64_t rows = (cuuint64_t)kHeads * kC;
    cuuint64_t dims[3] = {64, rows, 2};
    cuuint64_t strides[2] = {256, 128};
    cuuint32_t box[3] = {64, (cuuint32_t)kTile, 2};
    cuuint32_t estr[3] = {1, 1, 1};
    enc(map, CU_TENSOR_MAP_DATA_TYPE_BFLOAT16, 3, const_cast<void*>(ptr), dims, strides, box, estr,
        CU_TENSOR_MAP_INTERLEAVE_NONE, CU_TENSOR_MAP_SWIZZLE_128B, L2PROMO, CU_TENSOR_MAP_FLOAT_OOB_FILL_NONE);
}

}

extern "C" void kernel_launch(void* const* d_in, const int* in_sizes, int n_in, void* d_out, int out_size) {
    (void)in_sizes; (void)n_in; (void)out_size;
    static EncodeTiledFn enc = nullptr;
    if (!enc) {
        void* fn = nullptr;
        cudaDriverEntryPointQueryResult qres;
        cudaGetDriverEntryPoint("cuTensorMapEncodeTiled", &fn, cudaEnableDefault, &qres);
        enc = (EncodeTiledFn)fn;
        cudaFuncSetAttribute(tree_attn_kernel, cudaFuncAttributeMaxDynamicSharedMemorySize, kSmemTotal);
    }
    CUtensorMap map_k, map_v;
    make_map(enc, &map_k, d_in[1]);
    make_map(enc, &map_v, d_in[2]);
    tree_attn_kernel<<<kCtas, kThreads, kSmemTotal>>>(
        map_k, map_v, (const __nv_bfloat16*)d_in[0], (const __nv_bfloat16*)d_in[3], (const __nv_bfloat16*)d_in[4],
        (const __nv_bfloat16*)d_in[5], (__nv_bfloat16*)d_out);
}
```

```cpp
#include <cuda_runtime.h>
#include <cuda_bf16.h>
#include <cuda.h>
#include <stdint.h>

#define STAGES 8
#define INFLIGHT 4
#define TAILT 4
#define BURST 1
#define AUX_FIRST 1
#define EVICT_FIRST 1
#define L2PROMO CU_TENSOR_MAP_L2_PROMOTION_L2_128B

#define FB 1
#define FB_R 4
#define FB_PERIOD 16
#define FB_OFF 0.3f
#define FB_GAIN 3.0f
#define FB_DEAD 0.6f
#define FB_MAXN 10
#define FB_UP 1
#define FB_DOWN 1
#define FB_LAST 232

namespace {

constexpr int kB = 32, kHkv = 16, kT = 8, kC = 2048, kD = 128;
constexpr int kHeads = kB * kHkv;
constexpr int kCtas = 128;
constexpr int kRounds = kHeads / kCtas;
constexpr int kTile = 64;
constexpr int kTilesPerHead = kC / kTile;
constexpr int kTileBytes = kTile * kD * 2;
constexpr int kLoads = kRounds * kTilesPerHead * 2;
constexpr int kNCW = 4;
constexpr int kThreads = (kNCW + 1 + (FB ? 1 : 0)) * 32;
constexpr int kFbEnd = 240;
constexpr unsigned kFbTotal = kCtas * kFbEnd / FB_R;
__device__ unsigned g_progress;
constexpr int kAuxBytes = 8320;
constexpr int kMainTiles = kTilesPerHead - TAILT;

constexpr int kSmemRing = 0;
constexpr int kSmemRed = kSmemRing + STAGES * kTileBytes;
constexpr int kSmemP = kSmemRed + kNCW * 16 * 512;
constexpr int kSmemAux = kSmemP + TAILT * kNCW * 512;
constexpr int kSmemML = kSmemAux + kRounds * kAuxBytes;
constexpr int kSmemBar = kSmemML + kNCW * 16 * 2 * 4;
constexpr int kSmemFb = kSmemBar + (2 * STAGES + kRounds) * 8;
constexpr int kSmemTotal = kSmemFb + 16;

#define TS(i)
#define SMID()

__device__ __forceinline__ uint32_t smem_u32(const void* p) { return (uint32_t)__cvta_generic_to_shared(p); }
__device__ __forceinline__ void mbar_init(uint32_t bar, int cnt) {
    asm volatile("mbarrier.init.shared::cta.b64 [%0], %1;" ::"r"(bar), "r"(cnt));
}
__device__ __forceinline__ void mbar_expect_tx(uint32_t bar, uint32_t bytes) {
    asm volatile("mbarrier.arrive.expect_tx.shared::cta.b64 _, [%0], %1;" ::"r"(bar), "r"(bytes) : "memory");
}
__device__ __forceinline__ void mbar_arrive(uint32_t bar) {
    asm volatile("mbarrier.arrive.shared::cta.b64 _, [%0];" ::"r"(bar) : "memory");
}
__device__ __forceinline__ bool mbar_try(uint32_t bar, uint32_t parity) {
    uint32_t ok;
    asm volatile(
        "{\n"
        ".reg .pred p;\n"
        "mbarrier.try_wait.parity.shared::cta.b64 p, [%1], %2;\n"
        "selp.u32 %0, 1, 0, p;\n"
        "}\n" : "=r"(ok) : "r"(bar), "r"(parity) : "memory");
    return ok != 0;
}
__device__ __forceinline__ void mbar_wait(uint32_t bar, uint32_t parity) {
    uint32_t spins = 0;
    while (!mbar_try(bar, parity)) {
        if (++spins > (1u << 24)) __trap();
    }
}
__device__ __forceinline__ void bulk_load(uint32_t dst, const void* src, uint32_t bytes, uint32_t bar) {
    asm volatile("cp.async.bulk.shared::cluster.global.mbarrier::complete_tx::bytes [%0], [%1], %2, [%3];"
                 ::"r"(dst), "l"(src), "r"(bytes), "r"(bar) : "memory");
}
__device__ __forceinline__ void bulk_store(void* dst, uint32_t src, uint32_t bytes) {
    asm volatile("cp.async.bulk.global.shared::cta.bulk_group [%0], [%1], %2;" ::"l"(dst), "r"(src), "r"(bytes) : "memory");
}
__device__ __forceinline__ void tma_load_3d(uint32_t dst, const CUtensorMap* map, int c1, uint32_t bar, uint64_t pol) {
    asm volatile("cp.async.bulk.tensor.3d.shared::cluster.global.mbarrier::complete_tx::bytes.L2::cache_hint [%0], [%1, {%3, %4, %3}], [%2], %5;"
                 ::"r"(dst), "l"((uint64_t)map), "r"(bar), "r"(0), "r"(c1), "l"(pol) : "memory");
}
__device__ __forceinline__ void ldsm_x4(uint32_t addr, uint32_t& r0, uint32_t& r1, uint32_t& r2, uint32_t& r3) {
    asm volatile("ldmatrix.sync.aligned.m8n8.x4.shared.b16 {%0,%1,%2,%3}, [%4];"
                 : "=r"(r0), "=r"(r1), "=r"(r2), "=r"(r3) : "r"(addr) : "memory");
}
__device__ __forceinline__ void ldsm_x4_t(uint32_t addr, uint32_t& r0, uint32_t& r1, uint32_t& r2, uint32_t& r3) {
    asm volatile("ldmatrix.sync.aligned.m8n8.x4.trans.shared.b16 {%0,%1,%2,%3}, [%4];"
                 : "=r"(r0), "=r"(r1), "=r"(r2), "=r"(r3) : "r"(addr) : "memory");
}
__device__ __forceinline__ void mma_16816(float (&c)[4], const uint32_t (&a)[4], uint32_t b0, uint32_t b1) {
    asm volatile("mma.sync.aligned.m16n8k16.row.col.f32.bf16.bf16.f32 {%0,%1,%2,%3}, {%4,%5,%6,%7}, {%8,%9}, {%0,%1,%2,%3};"
                 : "+f"(c[0]), "+f"(c[1]), "+f"(c[2]), "+f"(c[3])
                 : "r"(a[0]), "r"(a[1]), "r"(a[2]), "r"(a[3]), "r"(b0), "r"(b1));
}
__device__ __forceinline__ void mma_1688(float (&c)[4], uint32_t a0, uint32_t a1, uint32_t b0) {
    asm volatile("mma.sync.aligned.m16n8k8.row.col.f32.bf16.bf16.f32 {%0,%1,%2,%3}, {%4,%5}, {%6}, {%0,%1,%2,%3};"
                 : "+f"(c[0]), "+f"(c[1]), "+f"(c[2]), "+f"(c[3])
                 : "r"(a0), "r"(a1), "r"(b0));
}
__device__ __forceinline__ uint32_t pack_bf16(float lo, float hi) {
    uint32_t r;
    asm("cvt.rn.bf16x2.f32 %0, %1, %2;" : "=r"(r) : "f"(hi), "f"(lo));
    return r;
}
__device__ __forceinline__ float ex2(float x) {
    float y;
    asm("ex2.approx.ftz.f32 %0, %1;" : "=f"(y) : "f"(x));
    return y;
}
__device__ __forceinline__ void consumer_sync() { asm volatile("bar.sync 1, %0;" ::"n"(kNCW * 32) : "memory"); }

__device__ __forceinline__ uint32_t tile_off(int r, int c) {
    return (uint32_t)((c >> 3) * (kTile * 128) + r * 128 + (((c & 7) ^ (r & 7)) << 4));
}

__device__ __forceinline__ void sts128(uint32_t addr, float a, float b, float c, float d) {
    asm volatile("st.shared.v4.f32 [%0], {%1,%2,%3,%4};" ::"r"(addr), "f"(a), "f"(b), "f"(c), "f"(d) : "memory");
}
__device__ __forceinline__ void sts128u(uint32_t addr, uint32_t a, uint32_t b, uint32_t c, uint32_t d) {
    asm volatile("st.shared.v4.b32 [%0], {%1,%2,%3,%4};" ::"r"(addr), "r"(a), "r"(b), "r"(c), "r"(d) : "memory");
}
__device__ __forceinline__ void lds128(uint32_t addr, float (&v)[4]) {
    asm volatile("ld.shared.v4.f32 {%0,%1,%2,%3}, [%4];" : "=f"(v[0]), "=f"(v[1]), "=f"(v[2]), "=f"(v[3]) : "r"(addr) : "memory");
}
__device__ __forceinline__ void lds128u(uint32_t addr, uint32_t (&v)[4]) {
    asm volatile("ld.shared.v4.b32 {%0,%1,%2,%3}, [%4];" : "=r"(v[0]), "=r"(v[1]), "=r"(v[2]), "=r"(v[3]) : "r"(addr) : "memory");
}

__global__ void __launch_bounds__(kThreads, 1)
tree_attn_kernel(const __grid_constant__ CUtensorMap map_k, const __grid_constant__ CUtensorMap map_v,
                 const __nv_bfloat16* __restrict__ q, const __nv_bfloat16* __restrict__ k_tree,
                 const __nv_bfloat16* __restrict__ v_tree, const __nv_bfloat16* __restrict__ tree_mask,
                 __nv_bfloat16* __restrict__ out) {
    extern __shared__ __align__(1024) unsigned char smem[];
    const uint32_t sbase = smem_u32(smem);
    const uint32_t bar_full = sbase + kSmemBar;
    const uint32_t bar_empty = bar_full + STAGES * 8;
    const uint32_t bar_aux = bar_empty + STAGES * 8;
    const int warp = threadIdx.x >> 5, lane = threadIdx.x & 31;
    const int cta = blockIdx.x;

    uint64_t pol = 0;
    auto issue_aux = [&](int r) {
        const int head = cta + r * kCtas;
        const uint32_t ab = sbase + kSmemAux + r * kAuxBytes;
        mbar_expect_tx(bar_aux + r * 8, kAuxBytes);
        bulk_load(ab, q + (size_t)head * 16 * kD, 4096, bar_aux + r * 8);
        bulk_load(ab + 4096, k_tree + (size_t)head * kT * kD, 2048, bar_aux + r * 8);
        bulk_load(ab + 6144, v_tree + (size_t)head * kT * kD, 2048, bar_aux + r * 8);
        bulk_load(ab + 8192, tree_mask + (head / kHkv) * kT * kT, 128, bar_aux + r * 8);
    };

    volatile int* fb = reinterpret_cast<volatile int*>(smem + kSmemFb);
    if (threadIdx.x == 0) { fb[0] = 0; fb[1] = 0; }
    if (threadIdx.x == kNCW * 32) {
        TS(0);
        asm volatile("createpolicy.fractional.L2::evict_first.b64 %0, 1.0;" : "=l"(pol));
#pragma unroll
        for (int s = 0; s < STAGES; s++) mbar_init(bar_full + s * 8, 1);
        mbar_init(bar_aux, 1);
        asm volatile("fence.mbarrier_init.release.cluster;" ::: "memory");
#pragma unroll
        for (int i = 0; i < INFLIGHT; i++) {
            mbar_expect_tx(bar_full + i * 8, kTileBytes);
            tma_load_3d(sbase + kSmemRing + i * kTileBytes, i >= TAILT ? &map_v : &map_k, cta * kC + (i % TAILT) * kTile, bar_full + i * 8, pol);
            if (AUX_FIRST && i == 0) issue_aux(0);
        }
        if (!AUX_FIRST) issue_aux(0);
        TS(1); SMID();
#pragma unroll
        for (int s = 0; s < STAGES; s++) mbar_init(bar_empty + s * 8, kNCW);
#pragma unroll
        for (int r = 1; r < kRounds; r++) mbar_init(bar_aux + r * 8, 1);
        asm volatile("fence.mbarrier_init.release.cluster;" ::: "memory");
    }
    __syncthreads();

    if (warp == kNCW) {
        if (lane == 0) {
            int s = INFLIGHT % STAGES; uint32_t ph = (INFLIGHT == STAGES) ? 0 : 1;
            int ls = 0; uint32_t lph = 0;
            int nconf = 0, depth = INFLIGHT, left = 0;
#pragma unroll 1
            for (int i = INFLIGHT; i < kLoads; i++) {
                const int j = i & 63;
                const bool is_v = (j / TAILT) & 1;
                const int tile = (j / (2 * TAILT)) * TAILT + (j % TAILT);
                const int row = (cta + (i >> 6) * kCtas) * kC + tile * kTile;
                {
                    const int cmd = fb[1];
                    if (cmd != 0) { fb[1] = 0; depth = INFLIGHT + (cmd > 0 ? FB_UP : -FB_DOWN); left = cmd > 0 ? cmd : -cmd; }
                    else if (left > 0 && --left == 0) depth = INFLIGHT;
                }
                while (i - nconf >= depth - ((BURST == 2 && !(i & 1)) ? 1 : 0)) {
                    mbar_wait(bar_full + ls * 8, lph);
                    if (++ls == STAGES) { ls = 0; lph ^= 1; }
                    nconf++;
                    fb[0] = nconf;
                    if (((nconf + cta) & (FB_R - 1)) == 0 && nconf <= kFbEnd)
                        asm volatile("red.relaxed.gpu.global.inc.u32 [%0], %1;" ::"l"(&g_progress), "r"(kFbTotal - 1) : "memory");
                }
                mbar_wait(bar_empty + s * 8, ph);
                mbar_expect_tx(bar_full + s * 8, kTileBytes);
                tma_load_3d(sbase + kSmemRing + s * kTileBytes, is_v ? &map_v : &map_k, row, bar_full + s * 8, pol);
                if (++s == STAGES) { s = 0; ph ^= 1; }
                if ((i & 63) == 40 && i < kLoads - 64) issue_aux((i >> 6) + 1);
            }
        }
    } else if (warp == kNCW + 1) {
        if (lane == 0) {
            float acc = 0.f; int ncmd = 0;
#pragma unroll 1
            for (int at = FB_LAST % FB_PERIOD + FB_PERIOD; at <= FB_LAST; at += FB_PERIOD) {
                int p0; uint32_t spins = 0;
                while ((p0 = fb[0]) < at) { __nanosleep(100); if (++spins > (1u << 22)) __trap(); }
                unsigned gv;
                asm volatile("ld.relaxed.gpu.global.u32 %0, [%1];" : "=r"(gv) : "l"(&g_progress) : "memory");
                const float lag = (float)gv * ((float)FB_R / kCtas) + FB_OFF - (float)p0;
                acc += lag;
                if (fabsf(lag) > FB_DEAD && lag > -64.f) {
                    int n = (int)(fminf(fabsf(lag) * FB_GAIN, (float)FB_MAXN) + 0.5f);
                    if (lag < 0.f) n = FB_DOWN ? -n : 0; else if (!FB_UP) n = 0;
                    fb[1] = n; ncmd += n < 0 ? -n : n;
                }
            }
        }
    } else {
        const float kScale = 0.08838834764831845f;
        const float kC2 = kScale * 1.4426950408889634f;
        const int g = lane >> 2, tq = lane & 3;
        int s = 0; uint32_t ph = 0;
        uint32_t koff[2][4], voff[8];
#pragma unroll
        for (int j = 0; j < 2; j++)
#pragma unroll
            for (int i = 0; i < 4; i++) koff[j][i] = tile_off(16 * warp + 8 * j + (lane & 7), 4 * i + (lane >> 3));
#pragma unroll
        for (int i = 0; i < 8; i++) voff[i] = tile_off(16 * warp + ((lane >> 3) & 1) * 8 + (lane & 7), 2 * i + (lane >> 4));
        uint32_t voff2[2];
#pragma unroll
        for (int i = 0; i < 2; i++) voff2[i] = tile_off(((lane >> 3) & 1) * 8 + (lane & 7), 4 * warp + 2 * i + (lane >> 4));
        const uint32_t red = sbase + kSmemRed + lane * 16, pbuf = sbase + kSmemP + lane * 16;
        float* mbuf = reinterpret_cast<float*>(smem + kSmemML);
        float* lbuf = mbuf + kNCW * 16;

#pragma unroll 1
        for (int r = 0; r < kRounds; r++) {
            const int head = cta + r * kCtas;
            uint32_t qf[8][4];
            float o[16][4];
            float m0 = -INFINITY, m1 = -INFINITY, l0 = 0.f, l1 = 0.f;
#pragma unroll
            for (int i = 0; i < 16; i++) { o[i][0] = 0.f; o[i][1] = 0.f; o[i][2] = 0.f; o[i][3] = 0.f; }

            const uint32_t ab = sbase + kSmemAux + r * kAuxBytes;
            mbar_wait(bar_aux + r * 8, 0);
#pragma unroll
            for (int ks = 0; ks < 8; ks++)
                ldsm_x4(ab + ((lane & 7) + ((lane >> 3) & 1) * 8) * 256 + (2 * ks + (lane >> 4)) * 16,
                        qf[ks][0], qf[ks][1], qf[ks][2], qf[ks][3]);
            if (warp == 0) {
                float sc[4] = {0.f, 0.f, 0.f, 0.f};
#pragma unroll
                for (int i = 0; i < 4; i++) {
                    uint32_t b0, b1, b2, b3;
                    ldsm_x4(ab + 4096 + (lane & 7) * 256 + (4 * i + (lane >> 3)) * 16, b0, b1, b2, b3);
                    mma_16816(sc, qf[2 * i], b0, b1);
                    mma_16816(sc, qf[2 * i + 1], b2, b3);
                }
                const uint32_t mraw = *reinterpret_cast<const uint32_t*>(smem + kSmemAux + r * kAuxBytes + 8192 + lane * 4);
                const float mk0 = __uint_as_float(mraw << 16), mk1 = __uint_as_float(mraw & 0xffff0000u);
                const float bias0 = (1.0f - mk0) * (-1000000000.0f / kScale);
                const float bias1 = (1.0f - mk1) * (-1000000000.0f / kScale);
                sc[0] += bias0; sc[1] += bias1; sc[2] += bias0; sc[3] += bias1;
                float mx0 = fmaxf(sc[0], sc[1]), mx1 = fmaxf(sc[2], sc[3]);
                mx0 = fmaxf(mx0, __shfl_xor_sync(0xffffffffu, mx0, 1));
                mx1 = fmaxf(mx1, __shfl_xor_sync(0xffffffffu, mx1, 1));
                mx0 = fmaxf(mx0, __shfl_xor_sync(0xffffffffu, mx0, 2));
                mx1 = fmaxf(mx1, __shfl_xor_sync(0xffffffffu, mx1, 2));
                m0 = mx0; m1 = mx1;
                const float p0 = ex2((sc[0] - m0) * kC2), p1 = ex2((sc[1] - m0) * kC2);
                const float p2 = ex2((sc[2] - m1) * kC2), p3 = ex2((sc[3] - m1) * kC2);
                l0 = p0 + p1; l1 = p2 + p3;
                const uint32_t pa0 = pack_bf16(p0, p1), pa1 = pack_bf16(p2, p3);
#pragma unroll
                for (int i = 0; i < 4; i++) {
                    uint32_t b0, b1, b2, b3;
                    ldsm_x4_t(ab + 6144 + (lane & 7) * 256 + (4 * i + (lane >> 3)) * 16, b0, b1, b2, b3);
                    mma_1688(o[4 * i + 0], pa0, pa1, b0);
                    mma_1688(o[4 * i + 1], pa0, pa1, b1);
                    mma_1688(o[4 * i + 2], pa0, pa1, b2);
                    mma_1688(o[4 * i + 3], pa0, pa1, b3);
                }
            }

            float st[TAILT][2][4];
            float mx0, mx1;
            auto scores = [&]() {
                mx0 = m0; mx1 = m1;
#pragma unroll
                for (int tt = 0; tt < TAILT; tt++) {
#pragma unroll
                    for (int j = 0; j < 2; j++) { st[tt][j][0] = 0.f; st[tt][j][1] = 0.f; st[tt][j][2] = 0.f; st[tt][j][3] = 0.f; }
                    const uint32_t kb = sbase + kSmemRing + s * kTileBytes;
                    mbar_wait(bar_full + s * 8, ph);
#pragma unroll
                    for (int i = 0; i < 4; i++) {
#pragma unroll
                        for (int j = 0; j < 2; j++) {
                            uint32_t b0, b1, b2, b3;
                            ldsm_x4(kb + koff[j][i], b0, b1, b2, b3);
                            mma_16816(st[tt][j], qf[2 * i], b0, b1);
                            mma_16816(st[tt][j], qf[2 * i + 1], b2, b3);
                        }
                    }
                    __syncwarp();
                    if (lane == 0) mbar_arrive(bar_empty + s * 8);
                    if (++s == STAGES) { s = 0; ph ^= 1; }
                    mx0 = fmaxf(mx0, fmaxf(fmaxf(st[tt][0][0], st[tt][0][1]), fmaxf(st[tt][1][0], st[tt][1][1])));
                    mx1 = fmaxf(mx1, fmaxf(fmaxf(st[tt][0][2], st[tt][0][3]), fmaxf(st[tt][1][2], st[tt][1][3])));
                }
                mx0 = fmaxf(mx0, __shfl_xor_sync(0xffffffffu, mx0, 1));
                mx1 = fmaxf(mx1, __shfl_xor_sync(0xffffffffu, mx1, 1));
                mx0 = fmaxf(mx0, __shfl_xor_sync(0xffffffffu, mx0, 2));
                mx1 = fmaxf(mx1, __shfl_xor_sync(0xffffffffu, mx1, 2));
            };

#pragma unroll 1
            for (int gi = 0; gi < kMainTiles / TAILT; gi++) {
                scores();
                if (threadIdx.x == 0 && r == 0 && gi == 0) TS(2);
                const float al0 = ex2((m0 - mx0) * kC2), al1 = ex2((m1 - mx1) * kC2);
                m0 = mx0; m1 = mx1;
                const float mb0 = mx0 * kC2, mb1 = mx1 * kC2;
                l0 *= al0; l1 *= al1;
                uint32_t pa[TAILT][4];
#pragma unroll
                for (int tt = 0; tt < TAILT; tt++) {
                    const float p00 = ex2(fmaf(st[tt][0][0], kC2, -mb0)), p01 = ex2(fmaf(st[tt][0][1], kC2, -mb0));
                    const float p02 = ex2(fmaf(st[tt][0][2], kC2, -mb1)), p03 = ex2(fmaf(st[tt][0][3], kC2, -mb1));
                    const float p10 = ex2(fmaf(st[tt][1][0], kC2, -mb0)), p11 = ex2(fmaf(st[tt][1][1], kC2, -mb0));
                    const float p12 = ex2(fmaf(st[tt][1][2], kC2, -mb1)), p13 = ex2(fmaf(st[tt][1][3], kC2, -mb1));
                    l0 += (p00 + p01) + (p10 + p11);
                    l1 += (p02 + p03) + (p12 + p13);
                    pa[tt][0] = pack_bf16(p00, p01); pa[tt][1] = pack_bf16(p02, p03);
                    pa[tt][2] = pack_bf16(p10, p11); pa[tt][3] = pack_bf16(p12, p13);
                }
#pragma unroll
                for (int i = 0; i < 16; i++) { o[i][0] *= al0; o[i][1] *= al0; o[i][2] *= al1; o[i][3] *= al1; }
#pragma unroll
                for (int tt = 0; tt < TAILT; tt++) {
                    const uint32_t vb = sbase + kSmemRing + s * kTileBytes;
                    mbar_wait(bar_full + s * 8, ph);
#pragma unroll
                    for (int i = 0; i < 8; i++) {
                        uint32_t b0, b1, b2, b3;
                        ldsm_x4_t(vb + voff[i], b0, b1, b2, b3);
                        mma_16816(o[2 * i], pa[tt], b0, b1);
                        mma_16816(o[2 * i + 1], pa[tt], b2, b3);
                    }
                    __syncwarp();
                    if (lane == 0) mbar_arrive(bar_empty + s * 8);
                    if (++s == STAGES) { s = 0; ph ^= 1; }
                }
            }

            scores();
            if (tq == 0) { mbuf[warp * 16 + g] = mx0; mbuf[warp * 16 + g + 8] = mx1; }
            consumer_sync();
#pragma unroll
            for (int w = 0; w < kNCW; w++) {
                mx0 = fmaxf(mx0, mbuf[w * 16 + g]);
                mx1 = fmaxf(mx1, mbuf[w * 16 + g + 8]);
            }
            {
                const float f0 = ex2((m0 - mx0) * kC2), f1 = ex2((m1 - mx1) * kC2);
                const float mb0 = mx0 * kC2, mb1 = mx1 * kC2;
                l0 *= f0; l1 *= f1;
#pragma unroll
                for (int tt = 0; tt < TAILT; tt++) {
                    const float p00 = ex2(fmaf(st[tt][0][0], kC2, -mb0)), p01 = ex2(fmaf(st[tt][0][1], kC2, -mb0));
                    const float p02 = ex2(fmaf(st[tt][0][2], kC2, -mb1)), p03 = ex2(fmaf(st[tt][0][3], kC2, -mb1));
                    const float p10 = ex2(fmaf(st[tt][1][0], kC2, -mb0)), p11 = ex2(fmaf(st[tt][1][1], kC2, -mb0));
                    const float p12 = ex2(fmaf(st[tt][1][2], kC2, -mb1)), p13 = ex2(fmaf(st[tt][1][3], kC2, -mb1));
                    l0 += (p00 + p01) + (p10 + p11);
                    l1 += (p02 + p03) + (p12 + p13);
                    sts128u(pbuf + (tt * kNCW + warp) * 512, pack_bf16(p00, p01), pack_bf16(p02, p03), pack_bf16(p10, p11), pack_bf16(p12, p13));
                }
                l0 += __shfl_xor_sync(0xffffffffu, l0, 1);
                l1 += __shfl_xor_sync(0xffffffffu, l1, 1);
                l0 += __shfl_xor_sync(0xffffffffu, l0, 2);
                l1 += __shfl_xor_sync(0xffffffffu, l1, 2);
                if (tq == 0) { lbuf[warp * 16 + g] = l0; lbuf[warp * 16 + g + 8] = l1; }
#pragma unroll
                for (int i = 0; i < 16; i++)
                    sts128(red + (warp * 16 + i) * 512, o[i][0] * f0, o[i][1] * f0, o[i][2] * f1, o[i][3] * f1);
            }
            consumer_sync();
            float oc[4][4];
            uint32_t pt[TAILT][kNCW][4];
#pragma unroll
            for (int i = 0; i < 4; i++) {
                lds128(red + (4 * warp + i) * 512, oc[i]);
#pragma unroll
                for (int w = 1; w < kNCW; w++) {
                    float v[4];
                    lds128(red + (w * 16 + 4 * warp + i) * 512, v);
                    oc[i][0] += v[0]; oc[i][1] += v[1]; oc[i][2] += v[2]; oc[i][3] += v[3];
                }
            }
#pragma unroll
            for (int tt = 0; tt < TAILT; tt++)
#pragma unroll
                for (int w = 0; w < kNCW; w++) lds128u(pbuf + (tt * kNCW + w) * 512, pt[tt][w]);
            const float inv0 = 1.0f / ((lbuf[g] + lbuf[16 + g]) + (lbuf[32 + g] + lbuf[48 + g]));
            const float inv1 = 1.0f / ((lbuf[g + 8] + lbuf[16 + g + 8]) + (lbuf[32 + g + 8] + lbuf[48 + g + 8]));
#pragma unroll
            for (int tt = 0; tt < TAILT; tt++) {
                const uint32_t vb = sbase + kSmemRing + s * kTileBytes;
                mbar_wait(bar_full + s * 8, ph);
                if (threadIdx.x == 0 && tt == TAILT - 1) TS(3);
#pragma unroll
                for (int w = 0; w < kNCW; w++) {
#pragma unroll
                    for (int i = 0; i < 2; i++) {
                        uint32_t b0, b1, b2, b3;
                        ldsm_x4_t(vb + voff2[i] + w * 2048, b0, b1, b2, b3);
                        mma_16816(oc[2 * i], pt[tt][w], b0, b1);
                        mma_16816(oc[2 * i + 1], pt[tt][w], b2, b3);
                    }
                }
                __syncwarp();
                if (lane == 0) mbar_arrive(bar_empty + s * 8);
                if (++s == STAGES) { s = 0; ph ^= 1; }
            }
            {
                uint32_t w[2][4];
#pragma unroll
                for (int i = 0; i < 4; i++) {
                    w[0][i] = pack_bf16(oc[i][0] * inv0, oc[i][1] * inv0);
                    w[1][i] = pack_bf16(oc[i][2] * inv1, oc[i][3] * inv1);
                }
                const bool hi = tq & 2, od = tq & 1;
#pragma unroll
                for (int h = 0; h < 2; h++) {
                    uint32_t a = hi ? w[h][0] : w[h][2], b = hi ? w[h][1] : w[h][3];
                    a = __shfl_xor_sync(0xffffffffu, a, 2);
                    b = __shfl_xor_sync(0xffffffffu, b, 2);
                    if (hi) { w[h][0] = a; w[h][1] = b; } else { w[h][2] = a; w[h][3] = b; }
                }
#pragma unroll
                for (int h = 0; h < 2; h++) {
                    uint32_t a = od ? w[h][0] : w[h][1], b = od ? w[h][2] : w[h][3];
                    a = __shfl_xor_sync(0xffffffffu, a, 1);
                    b = __shfl_xor_sync(0xffffffffu, b, 1);
                    if (od) { w[h][0] = a; w[h][2] = b; } else { w[h][1] = a; w[h][3] = b; }
                }
                uint4* o0 = reinterpret_cast<uint4*>(out + ((size_t)head * 16 + g) * kD + 32 * warp) + tq;
                o0[0] = make_uint4(w[0][0], w[0][1], w[0][2], w[0][3]);
                o0[8 * kD / 8] = make_uint4(w[1][0], w[1][1], w[1][2], w[1][3]);
            }
            if (threadIdx.x == 0) TS(4);
        }
    }
}

typedef CUresult (*EncodeTiledFn)(CUtensorMap*, CUtensorMapDataType, cuuint32_t, void*, const cuuint64_t*, const cuuint64_t*,
                                  const cuuint32_t*, const cuuint32_t*, CUtensorMapInterleave, CUtensorMapSwizzle,
                                  CUtensorMapL2promotion, CUtensorMapFloatOOBfill);

void make_map(EncodeTiledFn enc, CUtensorMap* map, const void* ptr) {
    const cuuint64_t rows = (cuuint64_t)kHeads * kC;
    cuuint64_t dims[3] = {64, rows, 2};
    cuuint64_t strides[2] = {256, 128};
    cuuint32_t box[3] = {64, (cuuint32_t)kTile, 2};
    cuuint32_t estr[3] = {1, 1, 1};
    enc(map, CU_TENSOR_MAP_DATA_TYPE_BFLOAT16, 3, const_cast<void*>(ptr), dims, strides, box, estr,
        CU_TENSOR_MAP_INTERLEAVE_NONE, CU_TENSOR_MAP_SWIZZLE_128B, L2PROMO, CU_TENSOR_MAP_FLOAT_OOB_FILL_NONE);
}

}

extern "C" void kernel_launch(void* const* d_in, const int* in_sizes, int n_in, void* d_out, int out_size) {
    (void)in_sizes; (void)n_in; (void)out_size;
    static EncodeTiledFn enc = nullptr;
    if (!enc) {
        void* fn = nullptr;
        cudaDriverEntryPointQueryResult qres;
        cudaGetDriverEntryPoint("cuTensorMapEncodeTiled", &fn, cudaEnableDefault, &qres);
        enc = (EncodeTiledFn)fn;
        cudaFuncSetAttribute(tree_attn_kernel, cudaFuncAttributeMaxDynamicSharedMemorySize, kSmemTotal);
    }
    CUtensorMap map_k, map_v;
    make_map(enc, &map_k, d_in[1]);
    make_map(enc, &map_v, d_in[2]);
    tree_attn_kernel<<<kCtas, kThreads, kSmemTotal>>>(
        map_k, map_v, (const __nv_bfloat16*)d_in[0], (const __nv_bfloat16*)d_in[3], (const __nv_bfloat16*)d_in[4],
        (const __nv_bfloat16*)d_in[5], (__nv_bfloat16*)d_out);
}
```

```cpp
#include <cuda_runtime.h>
#include <cuda_bf16.h>
#include <cuda.h>
#include <stdint.h>

namespace {

constexpr int kB = 32, kHkv = 16, kT = 8, kC = 2048, kD = 128;
constexpr int kHeads = kB * kHkv;
constexpr int kCtas = 128;
constexpr int kRounds = kHeads / kCtas;
constexpr int kTile = 64;
constexpr int kTileBytes = kTile * kD * 2;
constexpr int kGrp = 4;
constexpr int kGroups = kC / (kTile * kGrp);
constexpr int kLoadsPerHead = 2 * kC / kTile;
constexpr int kLoads = kRounds * kLoadsPerHead;
constexpr int kStages = 8;
constexpr int kInflight = 4;
constexpr int kNCW = 4;
constexpr int kThreads = (kNCW + 2) * 32;
constexpr int kAuxBytes = 8320;
constexpr int kAuxAt = 40;

constexpr int kFbEvery = 4;
constexpr int kFbEnd = 240;
constexpr unsigned kFbTotal = kCtas * (kFbEnd / kFbEvery);
constexpr int kFbPeriod = 16, kFbFirst = 24, kFbLast = 232;

constexpr int kSmemRing = 0;
constexpr int kSmemRed = kSmemRing + kStages * kTileBytes;
constexpr int kSmemP = kSmemRed + kNCW * 16 * 512;
constexpr int kSmemAux = kSmemP + kGrp * kNCW * 512;
constexpr int kSmemML = kSmemAux + kRounds * kAuxBytes;
constexpr int kSmemBar = kSmemML + kNCW * 16 * 2 * 4;
constexpr int kSmemFb = kSmemBar + (2 * kStages + kRounds) * 8;
constexpr int kSmemTotal = kSmemFb + 16;

__device__ unsigned g_progress;

#define TS(i)

__device__ __forceinline__ uint32_t smem_u32(const void* p) { return (uint32_t)__cvta_generic_to_shared(p); }
__device__ __forceinline__ void mbar_init(uint32_t bar, int cnt) {
    asm volatile("mbarrier.init.shared::cta.b64 [%0], %1;" ::"r"(bar), "r"(cnt));
}
__device__ __forceinline__ void mbar_expect_tx(uint32_t bar, uint32_t bytes) {
    asm volatile("mbarrier.arrive.expect_tx.shared::cta.b64 _, [%0], %1;" ::"r"(bar), "r"(bytes) : "memory");
}
__device__ __forceinline__ void mbar_arrive(uint32_t bar) {
    asm volatile("mbarrier.arrive.shared::cta.b64 _, [%0];" ::"r"(bar) : "memory");
}
__device__ __forceinline__ bool mbar_try(uint32_t bar, uint32_t parity) {
    uint32_t ok;
    asm volatile(
        "{\n"
        ".reg .pred p;\n"
        "mbarrier.try_wait.parity.shared::cta.b64 p, [%1], %2;\n"
        "selp.u32 %0, 1, 0, p;\n"
        "}\n" : "=r"(ok) : "r"(bar), "r"(parity) : "memory");
    return ok != 0;
}
__device__ __forceinline__ void mbar_wait(uint32_t bar, uint32_t parity) {
    uint32_t spins = 0;
    while (!mbar_try(bar, parity)) {
        if (++spins > (1u << 24)) __trap();
    }
}
__device__ __forceinline__ void bulk_load(uint32_t dst, const void* src, uint32_t bytes, uint32_t bar) {
    asm volatile("cp.async.bulk.shared::cluster.global.mbarrier::complete_tx::bytes [%0], [%1], %2, [%3];"
                 ::"r"(dst), "l"(src), "r"(bytes), "r"(bar) : "memory");
}
__device__ __forceinline__ void tma_load_tile(uint32_t dst, const CUtensorMap* map, int row, uint32_t bar, uint64_t pol) {
    asm volatile("cp.async.bulk.tensor.3d.shared::cluster.global.mbarrier::complete_tx::bytes.L2::cache_hint"
                 " [%0], [%1, {%3, %4, %3}], [%2], %5;"
                 ::"r"(dst), "l"((uint64_t)map), "r"(bar), "r"(0), "r"(row), "l"(pol) : "memory");
}
__device__ __forceinline__ void ldsm_x4(uint32_t addr, uint32_t& r0, uint32_t& r1, uint32_t& r2, uint32_t& r3) {
    asm volatile("ldmatrix.sync.aligned.m8n8.x4.shared.b16 {%0,%1,%2,%3}, [%4];"
                 : "=r"(r0), "=r"(r1), "=r"(r2), "=r"(r3) : "r"(addr) : "memory");
}
__device__ __forceinline__ void ldsm_x4_t(uint32_t addr, uint32_t& r0, uint32_t& r1, uint32_t& r2, uint32_t& r3) {
    asm volatile("ldmatrix.sync.aligned.m8n8.x4.trans.shared.b16 {%0,%1,%2,%3}, [%4];"
                 : "=r"(r0), "=r"(r1), "=r"(r2), "=r"(r3) : "r"(addr) : "memory");
}
__device__ __forceinline__ void mma_16816(float (&c)[4], const uint32_t (&a)[4], uint32_t b0, uint32_t b1) {
    asm volatile("mma.sync.aligned.m16n8k16.row.col.f32.bf16.bf16.f32 {%0,%1,%2,%3}, {%4,%5,%6,%7}, {%8,%9}, {%0,%1,%2,%3};"
                 : "+f"(c[0]), "+f"(c[1]), "+f"(c[2]), "+f"(c[3])
                 : "r"(a[0]), "r"(a[1]), "r"(a[2]), "r"(a[3]), "r"(b0), "r"(b1));
}
__device__ __forceinline__ void mma_1688(float (&c)[4], uint32_t a0, uint32_t a1, uint32_t b0) {
    asm volatile("mma.sync.aligned.m16n8k8.row.col.f32.bf16.bf16.f32 {%0,%1,%2,%3}, {%4,%5}, {%6}, {%0,%1,%2,%3};"
                 : "+f"(c[0]), "+f"(c[1]), "+f"(c[2]), "+f"(c[3])
                 : "r"(a0), "r"(a1), "r"(b0));
}
__device__ __forceinline__ uint32_t pack_bf16(float lo, float hi) {
    uint32_t r;
    asm("cvt.rn.bf16x2.f32 %0, %1, %2;" : "=r"(r) : "f"(hi), "f"(lo));
    return r;
}
__device__ __forceinline__ float ex2(float x) {
    float y;
    asm("ex2.approx.ftz.f32 %0, %1;" : "=f"(y) : "f"(x));
    return y;
}
__device__ __forceinline__ void sts128(uint32_t addr, float a, float b, float c, float d) {
    asm volatile("st.shared.v4.f32 [%0], {%1,%2,%3,%4};" ::"r"(addr), "f"(a), "f"(b), "f"(c), "f"(d) : "memory");
}
__device__ __forceinline__ void sts128u(uint32_t addr, const uint32_t (&v)[4]) {
    asm volatile("st.shared.v4.b32 [%0], {%1,%2,%3,%4};" ::"r"(addr), "r"(v[0]), "r"(v[1]), "r"(v[2]), "r"(v[3]) : "memory");
}
__device__ __forceinline__ void lds128(uint32_t addr, float (&v)[4]) {
    asm volatile("ld.shared.v4.f32 {%0,%1,%2,%3}, [%4];" : "=f"(v[0]), "=f"(v[1]), "=f"(v[2]), "=f"(v[3]) : "r"(addr) : "memory");
}
__device__ __forceinline__ void lds128u(uint32_t addr, uint32_t (&v)[4]) {
    asm volatile("ld.shared.v4.b32 {%0,%1,%2,%3}, [%4];" : "=r"(v[0]), "=r"(v[1]), "=r"(v[2]), "=r"(v[3]) : "r"(addr) : "memory");
}
__device__ __forceinline__ void consumer_sync() { asm volatile("bar.sync 1, %0;" ::"n"(kNCW * 32) : "memory"); }
__device__ __forceinline__ float quad_max(float v) {
    v = fmaxf(v, __shfl_xor_sync(0xffffffffu, v, 1));
    return fmaxf(v, __shfl_xor_sync(0xffffffffu, v, 2));
}
__device__ __forceinline__ float quad_sum(float v) {
    v += __shfl_xor_sync(0xffffffffu, v, 1);
    return v + __shfl_xor_sync(0xffffffffu, v, 2);
}

__device__ __forceinline__ uint32_t tile_off(int r, int c) {
    return (uint32_t)((c >> 3) * (kTile * 128) + r * 128 + (((c & 7) ^ (r & 7)) << 4));
}

__global__ void __launch_bounds__(kThreads, 1)
tree_attn_kernel(const __grid_constant__ CUtensorMap map_k, const __grid_constant__ CUtensorMap map_v,
                 const __nv_bfloat16* __restrict__ k_cache, const __nv_bfloat16* __restrict__ q,
                 const __nv_bfloat16* __restrict__ k_tree, const __nv_bfloat16* __restrict__ v_tree,
                 const __nv_bfloat16* __restrict__ tree_mask, __nv_bfloat16* __restrict__ out) {
    extern __shared__ __align__(1024) unsigned char smem[];
    const int cta = blockIdx.x;
    if (threadIdx.x == 0)
        asm volatile("cp.async.bulk.prefetch.L2.global [%0], %1;" ::"l"(k_cache + (size_t)cta * kC * kD), "r"(kTileBytes) : "memory");

    const uint32_t sbase = smem_u32(smem);
    const uint32_t bar_full = sbase + kSmemBar;
    const uint32_t bar_empty = bar_full + kStages * 8;
    const uint32_t bar_aux = bar_empty + kStages * 8;
    const int warp = threadIdx.x >> 5, lane = threadIdx.x & 31;
    volatile int* fb = reinterpret_cast<volatile int*>(smem + kSmemFb);

    uint64_t pol = 0;
    auto issue_aux = [&](int r) {
        const int head = cta + r * kCtas;
        const uint32_t ab = sbase + kSmemAux + r * kAuxBytes;
        mbar_expect_tx(bar_aux + r * 8, kAuxBytes);
        bulk_load(ab, q + (size_t)head * 16 * kD, 4096, bar_aux + r * 8);
        bulk_load(ab + 4096, k_tree + (size_t)head * kT * kD, 2048, bar_aux + r * 8);
        bulk_load(ab + 6144, v_tree + (size_t)head * kT * kD, 2048, bar_aux + r * 8);
        bulk_load(ab + 8192, tree_mask + (head / kHkv) * kT * kT, 128, bar_aux + r * 8);
    };

    if (threadIdx.x == 32) { fb[0] = 0; fb[1] = 0; }
    if (threadIdx.x == kNCW * 32) {
        TS(0);
        asm volatile("createpolicy.fractional.L2::evict_first.b64 %0, 1.0;" : "=l"(pol));
#pragma unroll
        for (int s = 0; s < kStages; s++) mbar_init(bar_full + s * 8, 1);
        mbar_init(bar_aux, 1);
        asm volatile("fence.mbarrier_init.release.cluster;" ::: "memory");
        static_assert(kInflight <= kGrp, "the first loads are K tiles");
#pragma unroll
        for (int i = 0; i < kInflight; i++) {
            mbar_expect_tx(bar_full + i * 8, kTileBytes);
            tma_load_tile(sbase + kSmemRing + i * kTileBytes, &map_k, cta * kC + i * kTile, bar_full + i * 8, pol);
            if (i == 0) issue_aux(0);
        }
        TS(1);
#pragma unroll
        for (int s = 0; s < kStages; s++) mbar_init(bar_empty + s * 8, kNCW);
#pragma unroll
        for (int r = 1; r < kRounds; r++) mbar_init(bar_aux + r * 8, 1);
        asm volatile("fence.mbarrier_init.release.cluster;" ::: "memory");
    }
    __syncthreads();

    if (warp == kNCW) {
        if (lane == 0) {
            int s = kInflight; uint32_t ph = 1;
            int ls = 0; uint32_t lph = 0;
            int landed = 0, depth = kInflight, left = 0;
#pragma unroll 1
            for (int i = kInflight; i < kLoads; i++) {
                const int j = i & (kLoadsPerHead - 1);
                const bool is_v = (j / kGrp) & 1;
                const int tile = (j / (2 * kGrp)) * kGrp + (j % kGrp);
                const int row = (cta + (i / kLoadsPerHead) * kCtas) * kC + tile * kTile;
                const int cmd = fb[1];
                if (cmd != 0) {
                    fb[1] = 0;
                    depth = cmd > 0 ? kInflight + 1 : kInflight - 1;
                    left = cmd > 0 ? cmd : -cmd;
                } else if (left > 0 && --left == 0) {
                    depth = kInflight;
                }
                while (i - landed >= depth) {
                    mbar_wait(bar_full + ls * 8, lph);
                    if (++ls == kStages) { ls = 0; lph ^= 1; }
                    fb[0] = ++landed;
                    if (((landed + cta) & (kFbEvery - 1)) == 0 && landed <= kFbEnd)
                        asm volatile("red.relaxed.gpu.global.inc.u32 [%0], %1;" ::"l"(&g_progress), "r"(kFbTotal - 1) : "memory");
                }
                mbar_wait(bar_empty + s * 8, ph);
                mbar_expect_tx(bar_full + s * 8, kTileBytes);
                tma_load_tile(sbase + kSmemRing + s * kTileBytes, is_v ? &map_v : &map_k, row, bar_full + s * 8, pol);
                if (++s == kStages) { s = 0; ph ^= 1; }
                if (j == kAuxAt && i < kLoads - kLoadsPerHead) issue_aux(i / kLoadsPerHead + 1);
            }
        }
    } else if (warp == kNCW + 1) {
        if (lane == 0) {
            uint32_t spins = 0;
#pragma unroll 1
            for (int at = kFbFirst; at <= kFbLast; at += kFbPeriod) {
                int mine;
                while ((mine = fb[0]) < at && ++spins < (1u << 22)) __nanosleep(100);
                unsigned total;
                asm volatile("ld.relaxed.gpu.global.u32 %0, [%1];" : "=r"(total) : "l"(&g_progress) : "memory");
                const float lag = (float)total * ((float)kFbEvery / kCtas) + 0.3f - (float)mine;
                if (fabsf(lag) > 0.6f && fabsf(lag) < 64.f) {
                    const int n = (int)(fminf(fabsf(lag) * 3.0f, 10.0f) + 0.5f);
                    fb[1] = lag > 0.f ? n : -n;
                }
            }
        }
    } else {
        const float kScale = 0.08838834764831845f;
        const float kC2 = kScale * 1.4426950408889634f;
        const int g = lane >> 2, tq = lane & 3;
        int s = 0; uint32_t ph = 0;
        uint32_t koff[4], voff[8], voff2[2];
#pragma unroll
        for (int i = 0; i < 4; i++) koff[i] = tile_off(16 * warp + (lane & 7), 4 * i + (lane >> 3));
#pragma unroll
        for (int i = 0; i < 8; i++) voff[i] = tile_off(16 * warp + ((lane >> 3) & 1) * 8 + (lane & 7), 2 * i + (lane >> 4));
#pragma unroll
        for (int i = 0; i < 2; i++) voff2[i] = tile_off(((lane >> 3) & 1) * 8 + (lane & 7), 4 * warp + 2 * i + (lane >> 4));
        const uint32_t red = sbase + kSmemRed + lane * 16, pbuf = sbase + kSmemP + lane * 16;
        float* mbuf = reinterpret_cast<float*>(smem + kSmemML);
        float* lbuf = mbuf + kNCW * 16;

#pragma unroll 1
        for (int r = 0; r < kRounds; r++) {
            const int head = cta + r * kCtas;
            uint32_t qf[8][4];
            float o[16][4];
            float m0 = -INFINITY, m1 = -INFINITY, l0 = 0.f, l1 = 0.f;
#pragma unroll
            for (int i = 0; i < 16; i++) { o[i][0] = 0.f; o[i][1] = 0.f; o[i][2] = 0.f; o[i][3] = 0.f; }

            const uint32_t ab = sbase + kSmemAux + r * kAuxBytes;
            mbar_wait(bar_aux + r * 8, 0);
#pragma unroll
            for (int ks = 0; ks < 8; ks++)
                ldsm_x4(ab + ((lane & 7) + ((lane >> 3) & 1) * 8) * 256 + (2 * ks + (lane >> 4)) * 16,
                        qf[ks][0], qf[ks][1], qf[ks][2], qf[ks][3]);
            if (warp == 0) {
                float sc[4] = {0.f, 0.f, 0.f, 0.f};
#pragma unroll
                for (int i = 0; i < 4; i++) {
                    uint32_t b0, b1, b2, b3;
                    ldsm_x4(ab + 4096 + (lane & 7) * 256 + (4 * i + (lane >> 3)) * 16, b0, b1, b2, b3);
                    mma_16816(sc, qf[2 * i], b0, b1);
                    mma_16816(sc, qf[2 * i + 1], b2, b3);
                }
                const uint32_t mraw = *reinterpret_cast<const uint32_t*>(smem + kSmemAux + r * kAuxBytes + 8192 + lane * 4);
                const float mk0 = __uint_as_float(mraw << 16), mk1 = __uint_as_float(mraw & 0xffff0000u);
                const float bias0 = (1.0f - mk0) * (-1000000000.0f / kScale);
                const float bias1 = (1.0f - mk1) * (-1000000000.0f / kScale);
                sc[0] += bias0; sc[1] += bias1; sc[2] += bias0; sc[3] += bias1;
                m0 = quad_max(fmaxf(sc[0], sc[1]));
                m1 = quad_max(fmaxf(sc[2], sc[3]));
                const float p0 = ex2((sc[0] - m0) * kC2), p1 = ex2((sc[1] - m0) * kC2);
                const float p2 = ex2((sc[2] - m1) * kC2), p3 = ex2((sc[3] - m1) * kC2);
                l0 = p0 + p1; l1 = p2 + p3;
                const uint32_t pa0 = pack_bf16(p0, p1), pa1 = pack_bf16(p2, p3);
#pragma unroll
                for (int i = 0; i < 4; i++) {
                    uint32_t b0, b1, b2, b3;
                    ldsm_x4_t(ab + 6144 + (lane & 7) * 256 + (4 * i + (lane >> 3)) * 16, b0, b1, b2, b3);
                    mma_1688(o[4 * i + 0], pa0, pa1, b0);
                    mma_1688(o[4 * i + 1], pa0, pa1, b1);
                    mma_1688(o[4 * i + 2], pa0, pa1, b2);
                    mma_1688(o[4 * i + 3], pa0, pa1, b3);
                }
            }

            float st[kGrp][2][4];
            float mx0, mx1;
            auto scores = [&]() {
                mx0 = m0; mx1 = m1;
#pragma unroll
                for (int t = 0; t < kGrp; t++) {
#pragma unroll
                    for (int j = 0; j < 2; j++) { st[t][j][0] = 0.f; st[t][j][1] = 0.f; st[t][j][2] = 0.f; st[t][j][3] = 0.f; }
                    const uint32_t kb = sbase + kSmemRing + s * kTileBytes;
                    mbar_wait(bar_full + s * 8, ph);
#pragma unroll
                    for (int i = 0; i < 4; i++) {
#pragma unroll
                        for (int j = 0; j < 2; j++) {
                            uint32_t b0, b1, b2, b3;
                            ldsm_x4(kb + koff[i] + j * 1024, b0, b1, b2, b3);
                            mma_16816(st[t][j], qf[2 * i], b0, b1);
                            mma_16816(st[t][j], qf[2 * i + 1], b2, b3);
                        }
                    }
                    __syncwarp();
                    if (lane == 0) mbar_arrive(bar_empty + s * 8);
                    if (++s == kStages) { s = 0; ph ^= 1; }
                    mx0 = fmaxf(mx0, fmaxf(fmaxf(st[t][0][0], st[t][0][1]), fmaxf(st[t][1][0], st[t][1][1])));
                    mx1 = fmaxf(mx1, fmaxf(fmaxf(st[t][0][2], st[t][0][3]), fmaxf(st[t][1][2], st[t][1][3])));
                }
                mx0 = quad_max(mx0);
                mx1 = quad_max(mx1);
            };
            auto probs = [&](int t, float mb0, float mb1, uint32_t (&pa)[4]) {
                const float p00 = ex2(fmaf(st[t][0][0], kC2, -mb0)), p01 = ex2(fmaf(st[t][0][1], kC2, -mb0));
                const float p02 = ex2(fmaf(st[t][0][2], kC2, -mb1)), p03 = ex2(fmaf(st[t][0][3], kC2, -mb1));
                const float p10 = ex2(fmaf(st[t][1][0], kC2, -mb0)), p11 = ex2(fmaf(st[t][1][1], kC2, -mb0));
                const float p12 = ex2(fmaf(st[t][1][2], kC2, -mb1)), p13 = ex2(fmaf(st[t][1][3], kC2, -mb1));
                l0 += (p00 + p01) + (p10 + p11);
                l1 += (p02 + p03) + (p12 + p13);
                pa[0] = pack_bf16(p00, p01); pa[1] = pack_bf16(p02, p03);
                pa[2] = pack_bf16(p10, p11); pa[3] = pack_bf16(p12, p13);
            };

#pragma unroll 1
            for (int gi = 0; gi < kGroups - 1; gi++) {
                scores();
                const float al0 = ex2((m0 - mx0) * kC2), al1 = ex2((m1 - mx1) * kC2);
                m0 = mx0; m1 = mx1;
                l0 *= al0; l1 *= al1;
                uint32_t pa[kGrp][4];
#pragma unroll
                for (int t = 0; t < kGrp; t++) probs(t, mx0 * kC2, mx1 * kC2, pa[t]);
#pragma unroll
                for (int i = 0; i < 16; i++) { o[i][0] *= al0; o[i][1] *= al0; o[i][2] *= al1; o[i][3] *= al1; }
#pragma unroll
                for (int t = 0; t < kGrp; t++) {
                    const uint32_t vb = sbase + kSmemRing + s * kTileBytes;
                    mbar_wait(bar_full + s * 8, ph);
#pragma unroll
                    for (int i = 0; i < 8; i++) {
                        uint32_t b0, b1, b2, b3;
                        ldsm_x4_t(vb + voff[i], b0, b1, b2, b3);
                        mma_16816(o[2 * i], pa[t], b0, b1);
                        mma_16816(o[2 * i + 1], pa[t], b2, b3);
                    }
                    __syncwarp();
                    if (lane == 0) mbar_arrive(bar_empty + s * 8);
                    if (++s == kStages) { s = 0; ph ^= 1; }
                }
            }

            scores();
            if (tq == 0) { mbuf[warp * 16 + g] = mx0; mbuf[warp * 16 + g + 8] = mx1; }
            consumer_sync();
#pragma unroll
            for (int w = 0; w < kNCW; w++) {
                mx0 = fmaxf(mx0, mbuf[w * 16 + g]);
                mx1 = fmaxf(mx1, mbuf[w * 16 + g + 8]);
            }
            {
                const float f0 = ex2((m0 - mx0) * kC2), f1 = ex2((m1 - mx1) * kC2);
                l0 *= f0; l1 *= f1;
#pragma unroll
                for (int t = 0; t < kGrp; t++) {
                    uint32_t pa[4];
                    probs(t, mx0 * kC2, mx1 * kC2, pa);
                    sts128u(pbuf + (t * kNCW + warp) * 512, pa);
                }
                l0 = quad_sum(l0);
                l1 = quad_sum(l1);
                if (tq == 0) { lbuf[warp * 16 + g] = l0; lbuf[warp * 16 + g + 8] = l1; }
#pragma unroll
                for (int i = 0; i < 16; i++)
                    sts128(red + (warp * 16 + i) * 512, o[i][0] * f0, o[i][1] * f0, o[i][2] * f1, o[i][3] * f1);
            }
            consumer_sync();
            float oc[4][4];
            uint32_t pt[kGrp][kNCW][4];
#pragma unroll
            for (int i = 0; i < 4; i++) {
                lds128(red + (4 * warp + i) * 512, oc[i]);
#pragma unroll
                for (int w = 1; w < kNCW; w++) {
                    float v[4];
                    lds128(red + (w * 16 + 4 * warp + i) * 512, v);
                    oc[i][0] += v[0]; oc[i][1] += v[1]; oc[i][2] += v[2]; oc[i][3] += v[3];
                }
            }
#pragma unroll
            for (int t = 0; t < kGrp; t++)
#pragma unroll
                for (int w = 0; w < kNCW; w++) lds128u(pbuf + (t * kNCW + w) * 512, pt[t][w]);
            const float inv0 = 1.0f / ((lbuf[g] + lbuf[16 + g]) + (lbuf[32 + g] + lbuf[48 + g]));
            const float inv1 = 1.0f / ((lbuf[g + 8] + lbuf[16 + g + 8]) + (lbuf[32 + g + 8] + lbuf[48 + g + 8]));
#pragma unroll
            for (int t = 0; t < kGrp; t++) {
                const uint32_t vb = sbase + kSmemRing + s * kTileBytes;
                mbar_wait(bar_full + s * 8, ph);
                if (threadIdx.x == 0 && t == kGrp - 1) TS(3);
#pragma unroll
                for (int w = 0; w < kNCW; w++) {
#pragma unroll
                    for (int i = 0; i < 2; i++) {
                        uint32_t b0, b1, b2, b3;
                        ldsm_x4_t(vb + voff2[i] + w * 2048, b0, b1, b2, b3);
                        mma_16816(oc[2 * i], pt[t][w], b0, b1);
                        mma_16816(oc[2 * i + 1], pt[t][w], b2, b3);
                    }
                }
                __syncwarp();
                if (lane == 0) mbar_arrive(bar_empty + s * 8);
                if (++s == kStages) { s = 0; ph ^= 1; }
            }
            {
                uint32_t w[2][4];
#pragma unroll
                for (int i = 0; i < 4; i++) {
                    w[0][i] = pack_bf16(oc[i][0] * inv0, oc[i][1] * inv0);
                    w[1][i] = pack_bf16(oc[i][2] * inv1, oc[i][3] * inv1);
                }
                const bool hi = tq & 2, od = tq & 1;
#pragma unroll
                for (int h = 0; h < 2; h++) {
                    uint32_t a = hi ? w[h][0] : w[h][2], b = hi ? w[h][1] : w[h][3];
                    a = __shfl_xor_sync(0xffffffffu, a, 2);
                    b = __shfl_xor_sync(0xffffffffu, b, 2);
                    if (hi) { w[h][0] = a; w[h][1] = b; } else { w[h][2] = a; w[h][3] = b; }
                }
#pragma unroll
                for (int h = 0; h < 2; h++) {
                    uint32_t a = od ? w[h][0] : w[h][1], b = od ? w[h][2] : w[h][3];
                    a = __shfl_xor_sync(0xffffffffu, a, 1);
                    b = __shfl_xor_sync(0xffffffffu, b, 1);
                    if (od) { w[h][0] = a; w[h][2] = b; } else { w[h][1] = a; w[h][3] = b; }
                }
                uint4* op = reinterpret_cast<uint4*>(out + ((size_t)head * 16 + g) * kD + 32 * warp) + tq;
                op[0] = make_uint4(w[0][0], w[0][1], w[0][2], w[0][3]);
                op[8 * kD / 8] = make_uint4(w[1][0], w[1][1], w[1][2], w[1][3]);
            }
            if (threadIdx.x == 0) TS(4);
        }
    }
}

typedef CUresult (*EncodeTiledFn)(CUtensorMap*, CUtensorMapDataType, cuuint32_t, void*, const cuuint64_t*, const cuuint64_t*,
                                  const cuuint32_t*, const cuuint32_t*, CUtensorMapInterleave, CUtensorMapSwizzle,
                                  CUtensorMapL2promotion, CUtensorMapFloatOOBfill);

void make_map(EncodeTiledFn enc, CUtensorMap* map, const void* ptr) {
    const cuuint64_t rows = (cuuint64_t)kHeads * kC;
    cuuint64_t dims[3] = {64, rows, 2};
    cuuint64_t strides[2] = {256, 128};
    cuuint32_t box[3] = {64, (cuuint32_t)kTile, 2};
    cuuint32_t estr[3] = {1, 1, 1};
    enc(map, CU_TENSOR_MAP_DATA_TYPE_BFLOAT16, 3, const_cast<void*>(ptr), dims, strides, box, estr,
        CU_TENSOR_MAP_INTERLEAVE_NONE, CU_TENSOR_MAP_SWIZZLE_128B, CU_TENSOR_MAP_L2_PROMOTION_L2_128B,
        CU_TENSOR_MAP_FLOAT_OOB_FILL_NONE);
}

}

extern "C" void kernel_launch(void* const* d_in, const int* in_sizes, int n_in, void* d_out, int out_size) {
    (void)in_sizes; (void)n_in; (void)out_size;
    static EncodeTiledFn enc = nullptr;
    if (!enc) {
        void* fn = nullptr;
        cudaDriverEntryPointQueryResult qres;
        cudaGetDriverEntryPoint("cuTensorMapEncodeTiled", &fn, cudaEnableDefault, &qres);
        enc = (EncodeTiledFn)fn;
        cudaFuncSetAttribute(tree_attn_kernel, cudaFuncAttributeMaxDynamicSharedMemorySize, kSmemTotal);
    }
    CUtensorMap map_k, map_v;
    make_map(enc, &map_k, d_in[1]);
    make_map(enc, &map_v, d_in[2]);
    tree_attn_kernel<<<kCtas, kThreads, kSmemTotal>>>(
        map_k, map_v, (const __nv_bfloat16*)d_in[1], (const __nv_bfloat16*)d_in[0], (const __nv_bfloat16*)d_in[3],
        (const __nv_bfloat16*)d_in[4], (const __nv_bfloat16*)d_in[5], (__nv_bfloat16*)d_out);
}
```

```cpp
#include <cuda_runtime.h>
#include <cuda_bf16.h>
#include <cuda.h>
#include <stdint.h>

namespace {

constexpr int kB = 32, kHkv = 16, kT = 8, kC = 2048, kD = 128;
constexpr int kHeads = kB * kHkv;
constexpr int kCtas = 128;
constexpr int kRounds = kHeads / kCtas;
constexpr int kTile = 64;
constexpr int kTileBytes = kTile * kD * 2;
constexpr int kGrp = 4;
constexpr int kGroups = kC / (kTile * kGrp);
constexpr int kLoadsPerHead = 2 * kC / kTile;
constexpr int kLoads = kRounds * kLoadsPerHead;
constexpr int kStages = 8;
constexpr int kInflight = 3;
constexpr int kNCW = 4;
constexpr int kThreads = (kNCW + 2) * 32;
constexpr int kAuxBytes = 8320;
constexpr int kAuxAt = 40;

constexpr int kFbEvery = 4;
constexpr int kFbEnd = 248;
constexpr unsigned kFbTotal = kCtas * (kFbEnd / kFbEvery);
constexpr int kFbPeriod = 8, kFbFirst = 16, kFbLast = 240;
static_assert(kFbEnd <= kLoads - kInflight - 1 && kFbEnd % kFbEvery == 0, "every CTA must make all of its reports");

constexpr int kSmemRing = 0;
constexpr int kSmemRed = kSmemRing + kStages * kTileBytes;
constexpr int kSmemP = kSmemRed + kNCW * 16 * 512;
constexpr int kSmemAux = kSmemP + kGrp * kNCW * 512;
constexpr int kSmemML = kSmemAux + kRounds * kAuxBytes;
constexpr int kSmemBar = kSmemML + kNCW * 16 * 2 * 4;
constexpr int kSmemFb = kSmemBar + (2 * kStages + kRounds) * 8;
constexpr int kSmemTotal = kSmemFb + 16;

__device__ unsigned g_progress;

#define TS(i)

__device__ __forceinline__ uint32_t smem_u32(const void* p) { return (uint32_t)__cvta_generic_to_shared(p); }
__device__ __forceinline__ void mbar_init(uint32_t bar, int cnt) {
    asm volatile("mbarrier.init.shared::cta.b64 [%0], %1;" ::"r"(bar), "r"(cnt));
}
__device__ __forceinline__ void mbar_expect_tx(uint32_t bar, uint32_t bytes) {
    asm volatile("mbarrier.arrive.expect_tx.shared::cta.b64 _, [%0], %1;" ::"r"(bar), "r"(bytes) : "memory");
}
__device__ __forceinline__ void mbar_arrive(uint32_t bar) {
    asm volatile("mbarrier.arrive.shared::cta.b64 _, [%0];" ::"r"(bar) : "memory");
}
__device__ __forceinline__ bool mbar_try(uint32_t bar, uint32_t parity) {
    uint32_t ok;
    asm volatile(
        "{\n"
        ".reg .pred p;\n"
        "mbarrier.try_wait.parity.shared::cta.b64 p, [%1], %2;\n"
        "selp.u32 %0, 1, 0, p;\n"
        "}\n" : "=r"(ok) : "r"(bar), "r"(parity) : "memory");
    return ok != 0;
}
__device__ __forceinline__ void mbar_wait(uint32_t bar, uint32_t parity) {
    uint32_t spins = 0;
    while (!mbar_try(bar, parity)) {
        if (++spins > (1u << 24)) __trap();
    }
}
__device__ __forceinline__ void bulk_load(uint32_t dst, const void* src, uint32_t bytes, uint32_t bar) {
    asm volatile("cp.async.bulk.shared::cluster.global.mbarrier::complete_tx::bytes [%0], [%1], %2, [%3];"
                 ::"r"(dst), "l"(src), "r"(bytes), "r"(bar) : "memory");
}
__device__ __forceinline__ void tma_load_tile(uint32_t dst, const CUtensorMap* map, int row, uint32_t bar, uint64_t pol) {
    asm volatile("cp.async.bulk.tensor.3d.shared::cluster.global.mbarrier::complete_tx::bytes.L2::cache_hint"
                 " [%0], [%1, {%3, %4, %3}], [%2], %5;"
                 ::"r"(dst), "l"((uint64_t)map), "r"(bar), "r"(0), "r"(row), "l"(pol) : "memory");
}
__device__ __forceinline__ void ldsm_x4(uint32_t addr, uint32_t& r0, uint32_t& r1, uint32_t& r2, uint32_t& r3) {
    asm volatile("ldmatrix.sync.aligned.m8n8.x4.shared.b16 {%0,%1,%2,%3}, [%4];"
                 : "=r"(r0), "=r"(r1), "=r"(r2), "=r"(r3) : "r"(addr) : "memory");
}
__device__ __forceinline__ void ldsm_x4_t(uint32_t addr, uint32_t& r0, uint32_t& r1, uint32_t& r2, uint32_t& r3) {
    asm volatile("ldmatrix.sync.aligned.m8n8.x4.trans.shared.b16 {%0,%1,%2,%3}, [%4];"
                 : "=r"(r0), "=r"(r1), "=r"(r2), "=r"(r3) : "r"(addr) : "memory");
}
__device__ __forceinline__ void mma_16816(float (&c)[4], const uint32_t (&a)[4], uint32_t b0, uint32_t b1) {
    asm volatile("mma.sync.aligned.m16n8k16.row.col.f32.bf16.bf16.f32 {%0,%1,%2,%3}, {%4,%5,%6,%7}, {%8,%9}, {%0,%1,%2,%3};"
                 : "+f"(c[0]), "+f"(c[1]), "+f"(c[2]), "+f"(c[3])
                 : "r"(a[0]), "r"(a[1]), "r"(a[2]), "r"(a[3]), "r"(b0), "r"(b1));
}
__device__ __forceinline__ void mma_1688(float (&c)[4], uint32_t a0, uint32_t a1, uint32_t b0) {
    asm volatile("mma.sync.aligned.m16n8k8.row.col.f32.bf16.bf16.f32 {%0,%1,%2,%3}, {%4,%5}, {%6}, {%0,%1,%2,%3};"
                 : "+f"(c[0]), "+f"(c[1]), "+f"(c[2]), "+f"(c[3])
                 : "r"(a0), "r"(a1), "r"(b0));
}
__device__ __forceinline__ uint32_t pack_bf16(float lo, float hi) {
    uint32_t r;
    asm("cvt.rn.bf16x2.f32 %0, %1, %2;" : "=r"(r) : "f"(hi), "f"(lo));
    return r;
}
__device__ __forceinline__ float ex2(float x) {
    float y;
    asm("ex2.approx.ftz.f32 %0, %1;" : "=f"(y) : "f"(x));
    return y;
}
__device__ __forceinline__ void sts128(uint32_t addr, float a, float b, float c, float d) {
    asm volatile("st.shared.v4.f32 [%0], {%1,%2,%3,%4};" ::"r"(addr), "f"(a), "f"(b), "f"(c), "f"(d) : "memory");
}
__device__ __forceinline__ void sts128u(uint32_t addr, const uint32_t (&v)[4]) {
    asm volatile("st.shared.v4.b32 [%0], {%1,%2,%3,%4};" ::"r"(addr), "r"(v[0]), "r"(v[1]), "r"(v[2]), "r"(v[3]) : "memory");
}
__device__ __forceinline__ void lds128(uint32_t addr, float (&v)[4]) {
    asm volatile("ld.shared.v4.f32 {%0,%1,%2,%3}, [%4];" : "=f"(v[0]), "=f"(v[1]), "=f"(v[2]), "=f"(v[3]) : "r"(addr) : "memory");
}
__device__ __forceinline__ void lds128u(uint32_t addr, uint32_t (&v)[4]) {
    asm volatile("ld.shared.v4.b32 {%0,%1,%2,%3}, [%4];" : "=r"(v[0]), "=r"(v[1]), "=r"(v[2]), "=r"(v[3]) : "r"(addr) : "memory");
}
__device__ __forceinline__ void consumer_sync() { asm volatile("bar.sync 1, %0;" ::"n"(kNCW * 32) : "memory"); }
__device__ __forceinline__ float quad_max(float v) {
    v = fmaxf(v, __shfl_xor_sync(0xffffffffu, v, 1));
    return fmaxf(v, __shfl_xor_sync(0xffffffffu, v, 2));
}
__device__ __forceinline__ float quad_sum(float v) {
    v += __shfl_xor_sync(0xffffffffu, v, 1);
    return v + __shfl_xor_sync(0xffffffffu, v, 2);
}

__device__ __forceinline__ uint32_t tile_off(int r, int c) {
    return (uint32_t)((c >> 3) * (kTile * 128) + r * 128 + (((c & 7) ^ (r & 7)) << 4));
}

__global__ void __launch_bounds__(kThreads, 1)
tree_attn_kernel(const __grid_constant__ CUtensorMap map_k, const __grid_constant__ CUtensorMap map_v,
                 const __nv_bfloat16* __restrict__ k_cache, const __nv_bfloat16* __restrict__ q,
                 const __nv_bfloat16* __restrict__ k_tree, const __nv_bfloat16* __restrict__ v_tree,
                 const __nv_bfloat16* __restrict__ tree_mask, __nv_bfloat16* __restrict__ out) {
    extern __shared__ __align__(1024) unsigned char smem[];
    const int cta = blockIdx.x;
    if (threadIdx.x == 0)
        asm volatile("cp.async.bulk.prefetch.L2.global [%0], %1;" ::"l"(k_cache + (size_t)cta * kC * kD), "r"(kTileBytes) : "memory");

    const uint32_t sbase = smem_u32(smem);
    const uint32_t bar_full = sbase + kSmemBar;
    const uint32_t bar_empty = bar_full + kStages * 8;
    const uint32_t bar_aux = bar_empty + kStages * 8;
    const int warp = threadIdx.x >> 5, lane = threadIdx.x & 31;
    volatile int* fb = reinterpret_cast<volatile int*>(smem + kSmemFb);

    uint64_t pol = 0;
    auto issue_aux = [&](int r) {
        const int head = cta + r * kCtas;
        const uint32_t ab = sbase + kSmemAux + r * kAuxBytes;
        mbar_expect_tx(bar_aux + r * 8, kAuxBytes);
        bulk_load(ab, q + (size_t)head * 16 * kD, 4096, bar_aux + r * 8);
        bulk_load(ab + 4096, k_tree + (size_t)head * kT * kD, 2048, bar_aux + r * 8);
        bulk_load(ab + 6144, v_tree + (size_t)head * kT * kD, 2048, bar_aux + r * 8);
        bulk_load(ab + 8192, tree_mask + (head / kHkv) * kT * kT, 128, bar_aux + r * 8);
    };

    if (threadIdx.x == 32) { fb[0] = 0; fb[1] = 0; }
    if (threadIdx.x == kNCW * 32) {
        TS(0);
        asm volatile("createpolicy.fractional.L2::evict_first.b64 %0, 1.0;" : "=l"(pol));
#pragma unroll
        for (int s = 0; s < kStages; s++) mbar_init(bar_full + s * 8, 1);
        mbar_init(bar_aux, 1);
        asm volatile("fence.mbarrier_init.release.cluster;" ::: "memory");
        static_assert(kInflight <= kGrp, "the first loads are K tiles");
#pragma unroll
        for (int i = 0; i < kInflight; i++) {
            mbar_expect_tx(bar_full + i * 8, kTileBytes);
            tma_load_tile(sbase + kSmemRing + i * kTileBytes, &map_k, cta * kC + i * kTile, bar_full + i * 8, pol);
            if (i == 0) issue_aux(0);
        }
        TS(1);
#pragma unroll
        for (int s = 0; s < kStages; s++) mbar_init(bar_empty + s * 8, kNCW);
#pragma unroll
        for (int r = 1; r < kRounds; r++) mbar_init(bar_aux + r * 8, 1);
        asm volatile("fence.mbarrier_init.release.cluster;" ::: "memory");
    }
    __syncthreads();

    if (warp == kNCW) {
        if (lane == 0) {
            int s = kInflight; uint32_t ph = 1;
            int ls = 0; uint32_t lph = 0;
            int landed = 0, depth = kInflight, left = 0;
#pragma unroll 1
            for (int i = kInflight; i < kLoads; i++) {
                const int j = i & (kLoadsPerHead - 1);
                const bool is_v = (j / kGrp) & 1;
                const int tile = (j / (2 * kGrp)) * kGrp + (j % kGrp);
                const int row = (cta + (i / kLoadsPerHead) * kCtas) * kC + tile * kTile;
                const int cmd = fb[1];
                if (cmd != 0) {
                    fb[1] = 0;
                    depth = cmd > 0 ? kInflight + 1 : kInflight - 1;
                    left = cmd > 0 ? cmd : -cmd;
                } else if (left > 0 && --left == 0) {
                    depth = kInflight;
                }
                while (i - landed >= depth) {
                    mbar_wait(bar_full + ls * 8, lph);
                    if (++ls == kStages) { ls = 0; lph ^= 1; }
                    fb[0] = ++landed;
                    if (((landed + cta) & (kFbEvery - 1)) == 0 && landed <= kFbEnd)
                        asm volatile("red.relaxed.gpu.global.inc.u32 [%0], %1;" ::"l"(&g_progress), "r"(kFbTotal - 1) : "memory");
                }
                mbar_wait(bar_empty + s * 8, ph);
                mbar_expect_tx(bar_full + s * 8, kTileBytes);
                tma_load_tile(sbase + kSmemRing + s * kTileBytes, is_v ? &map_v : &map_k, row, bar_full + s * 8, pol);
                if (++s == kStages) { s = 0; ph ^= 1; }
                if (j == kAuxAt && i < kLoads - kLoadsPerHead) issue_aux(i / kLoadsPerHead + 1);
            }
        }
    } else if (warp == kNCW + 1) {
        if (lane == 0) {
            uint32_t spins = 0;
            float integ = 0.f;
#pragma unroll 1
            for (int at = kFbFirst; at <= kFbLast; at += kFbPeriod) {
                int mine;
                while ((mine = fb[0]) < at && ++spins < (1u << 22)) __nanosleep(100);
                unsigned total;
                asm volatile("ld.relaxed.gpu.global.u32 %0, [%1];" : "=r"(total) : "l"(&g_progress) : "memory");
                const float lag = (float)total * ((float)kFbEvery / kCtas) + 0.3f - (float)mine;
                if (fabsf(lag) < 64.f) {
                    integ = fminf(fmaxf(integ + 0.2f * lag, -8.f), 8.f);
                    const float u = 2.0f * lag + integ;
                    if (fabsf(u) > 1.0f) {
                        const int n = (int)(fminf(fabsf(u), 5.0f) + 0.5f);
                        fb[1] = u > 0.f ? n : -n;
                    }
                }
            }
        }
    } else {
        const float kScale = 0.08838834764831845f;
        const float kC2 = kScale * 1.4426950408889634f;
        const int g = lane >> 2, tq = lane & 3;
        int s = 0; uint32_t ph = 0;
        uint32_t koff[4], voff[8], voff2[2];
#pragma unroll
        for (int i = 0; i < 4; i++) koff[i] = tile_off(16 * warp + (lane & 7), 4 * i + (lane >> 3));
#pragma unroll
        for (int i = 0; i < 8; i++) voff[i] = tile_off(16 * warp + ((lane >> 3) & 1) * 8 + (lane & 7), 2 * i + (lane >> 4));
#pragma unroll
        for (int i = 0; i < 2; i++) voff2[i] = tile_off(((lane >> 3) & 1) * 8 + (lane & 7), 4 * warp + 2 * i + (lane >> 4));
        const uint32_t red = sbase + kSmemRed + lane * 16, pbuf = sbase + kSmemP + lane * 16;
        float* mbuf = reinterpret_cast<float*>(smem + kSmemML);
        float* lbuf = mbuf + kNCW * 16;

#pragma unroll 1
        for (int r = 0; r < kRounds; r++) {
            const int head = cta + r * kCtas;
            uint32_t qf[8][4];
            float o[16][4];
            float m0 = -INFINITY, m1 = -INFINITY, l0 = 0.f, l1 = 0.f;
#pragma unroll
            for (int i = 0; i < 16; i++) { o[i][0] = 0.f; o[i][1] = 0.f; o[i][2] = 0.f; o[i][3] = 0.f; }

            const uint32_t ab = sbase + kSmemAux + r * kAuxBytes;
            mbar_wait(bar_aux + r * 8, 0);
#pragma unroll
            for (int ks = 0; ks < 8; ks++)
                ldsm_x4(ab + ((lane & 7) + ((lane >> 3) & 1) * 8) * 256 + (2 * ks + (lane >> 4)) * 16,
                        qf[ks][0], qf[ks][1], qf[ks][2], qf[ks][3]);
            if (warp == 0) {
                float sc[4] = {0.f, 0.f, 0.f, 0.f};
#pragma unroll
                for (int i = 0; i < 4; i++) {
                    uint32_t b0, b1, b2, b3;
                    ldsm_x4(ab + 4096 + (lane & 7) * 256 + (4 * i + (lane >> 3)) * 16, b0, b1, b2, b3);
                    mma_16816(sc, qf[2 * i], b0, b1);
                    mma_16816(sc, qf[2 * i + 1], b2, b3);
                }
                const uint32_t mraw = *reinterpret_cast<const uint32_t*>(smem + kSmemAux + r * kAuxBytes + 8192 + lane * 4);
                const float mk0 = __uint_as_float(mraw << 16), mk1 = __uint_as_float(mraw & 0xffff0000u);
                const float bias0 = (1.0f - mk0) * (-1000000000.0f / kScale);
                const float bias1 = (1.0f - mk1) * (-1000000000.0f / kScale);
                sc[0] += bias0; sc[1] += bias1; sc[2] += bias0; sc[3] += bias1;
                m0 = quad_max(fmaxf(sc[0], sc[1]));
                m1 = quad_max(fmaxf(sc[2], sc[3]));
                const float p0 = ex2((sc[0] - m0) * kC2), p1 = ex2((sc[1] - m0) * kC2);
                const float p2 = ex2((sc[2] - m1) * kC2), p3 = ex2((sc[3] - m1) * kC2);
                l0 = p0 + p1; l1 = p2 + p3;
                const uint32_t pa0 = pack_bf16(p0, p1), pa1 = pack_bf16(p2, p3);
#pragma unroll
                for (int i = 0; i < 4; i++) {
                    uint32_t b0, b1, b2, b3;
                    ldsm_x4_t(ab + 6144 + (lane & 7) * 256 + (4 * i + (lane >> 3)) * 16, b0, b1, b2, b3);
                    mma_1688(o[4 * i + 0], pa0, pa1, b0);
                    mma_1688(o[4 * i + 1], pa0, pa1, b1);
                    mma_1688(o[4 * i + 2], pa0, pa1, b2);
                    mma_1688(o[4 * i + 3], pa0, pa1, b3);
                }
            }

            float st[kGrp][2][4];
            float mx0, mx1;
            auto scores = [&]() {
                mx0 = m0; mx1 = m1;
#pragma unroll
                for (int t = 0; t < kGrp; t++) {
#pragma unroll
                    for (int j = 0; j < 2; j++) { st[t][j][0] = 0.f; st[t][j][1] = 0.f; st[t][j][2] = 0.f; st[t][j][3] = 0.f; }
                    const uint32_t kb = sbase + kSmemRing + s * kTileBytes;
                    mbar_wait(bar_full + s * 8, ph);
#pragma unroll
                    for (int i = 0; i < 4; i++) {
#pragma unroll
                        for (int j = 0; j < 2; j++) {
                            uint32_t b0, b1, b2, b3;
                            ldsm_x4(kb + koff[i] + j * 1024, b0, b1, b2, b3);
                            mma_16816(st[t][j], qf[2 * i], b0, b1);
                            mma_16816(st[t][j], qf[2 * i + 1], b2, b3);
                        }
                    }
                    __syncwarp();
                    if (lane == 0) mbar_arrive(bar_empty + s * 8);
                    if (++s == kStages) { s = 0; ph ^= 1; }
                    mx0 = fmaxf(mx0, fmaxf(fmaxf(st[t][0][0], st[t][0][1]), fmaxf(st[t][1][0], st[t][1][1])));
                    mx1 = fmaxf(mx1, fmaxf(fmaxf(st[t][0][2], st[t][0][3]), fmaxf(st[t][1][2], st[t][1][3])));
                }
                mx0 = quad_max(mx0);
                mx1 = quad_max(mx1);
            };
            auto probs = [&](int t, float mb0, float mb1, uint32_t (&pa)[4]) {
                const float p00 = ex2(fmaf(st[t][0][0], kC2, -mb0)), p01 = ex2(fmaf(st[t][0][1], kC2, -mb0));
                const float p02 = ex2(fmaf(st[t][0][2], kC2, -mb1)), p03 = ex2(fmaf(st[t][0][3], kC2, -mb1));
                const float p10 = ex2(fmaf(st[t][1][0], kC2, -mb0)), p11 = ex2(fmaf(st[t][1][1], kC2, -mb0));
                const float p12 = ex2(fmaf(st[t][1][2], kC2, -mb1)), p13 = ex2(fmaf(st[t][1][3], kC2, -mb1));
                l0 += (p00 + p01) + (p10 + p11);
                l1 += (p02 + p03) + (p12 + p13);
                pa[0] = pack_bf16(p00, p01); pa[1] = pack_bf16(p02, p03);
                pa[2] = pack_bf16(p10, p11); pa[3] = pack_bf16(p12, p13);
            };

#pragma unroll 1
            for (int gi = 0; gi < kGroups - 1; gi++) {
                scores();
                const float al0 = ex2((m0 - mx0) * kC2), al1 = ex2((m1 - mx1) * kC2);
                m0 = mx0; m1 = mx1;
                l0 *= al0; l1 *= al1;
                uint32_t pa[kGrp][4];
#pragma unroll
                for (int t = 0; t < kGrp; t++) probs(t, mx0 * kC2, mx1 * kC2, pa[t]);
#pragma unroll
                for (int i = 0; i < 16; i++) { o[i][0] *= al0; o[i][1] *= al0; o[i][2] *= al1; o[i][3] *= al1; }
#pragma unroll
                for (int t = 0; t < kGrp; t++) {
                    const uint32_t vb = sbase + kSmemRing + s * kTileBytes;
                    mbar_wait(bar_full + s * 8, ph);
#pragma unroll
                    for (int i = 0; i < 8; i++) {
                        uint32_t b0, b1, b2, b3;
                        ldsm_x4_t(vb + voff[i], b0, b1, b2, b3);
                        mma_16816(o[2 * i], pa[t], b0, b1);
                        mma_16816(o[2 * i + 1], pa[t], b2, b3);
                    }
                    __syncwarp();
                    if (lane == 0) mbar_arrive(bar_empty + s * 8);
                    if (++s == kStages) { s = 0; ph ^= 1; }
                }
            }

            scores();
            if (tq == 0) { mbuf[warp * 16 + g] = mx0; mbuf[warp * 16 + g + 8] = mx1; }
            consumer_sync();
#pragma unroll
            for (int w = 0; w < kNCW; w++) {
                mx0 = fmaxf(mx0, mbuf[w * 16 + g]);
                mx1 = fmaxf(mx1, mbuf[w * 16 + g + 8]);
            }
            {
                const float f0 = ex2((m0 - mx0) * kC2), f1 = ex2((m1 - mx1) * kC2);
                l0 *= f0; l1 *= f1;
#pragma unroll
                for (int t = 0; t < kGrp; t++) {
                    uint32_t pa[4];
                    probs(t, mx0 * kC2, mx1 * kC2, pa);
                    sts128u(pbuf + (t * kNCW + warp) * 512, pa);
                }
                l0 = quad_sum(l0);
                l1 = quad_sum(l1);
                if (tq == 0) { lbuf[warp * 16 + g] = l0; lbuf[warp * 16 + g + 8] = l1; }
#pragma unroll
                for (int i = 0; i < 16; i++)
                    sts128(red + (warp * 16 + i) * 512, o[i][0] * f0, o[i][1] * f0, o[i][2] * f1, o[i][3] * f1);
            }
            consumer_sync();
            float oc[4][4];
            uint32_t pt[kGrp][kNCW][4];
#pragma unroll
            for (int i = 0; i < 4; i++) {
                lds128(red + (4 * warp + i) * 512, oc[i]);
#pragma unroll
                for (int w = 1; w < kNCW; w++) {
                    float v[4];
                    lds128(red + (w * 16 + 4 * warp + i) * 512, v);
                    oc[i][0] += v[0]; oc[i][1] += v[1]; oc[i][2] += v[2]; oc[i][3] += v[3];
                }
            }
#pragma unroll
            for (int t = 0; t < kGrp; t++)
#pragma unroll
                for (int w = 0; w < kNCW; w++) lds128u(pbuf + (t * kNCW + w) * 512, pt[t][w]);
            const float inv0 = 1.0f / ((lbuf[g] + lbuf[16 + g]) + (lbuf[32 + g] + lbuf[48 + g]));
            const float inv1 = 1.0f / ((lbuf[g + 8] + lbuf[16 + g + 8]) + (lbuf[32 + g + 8] + lbuf[48 + g + 8]));
#pragma unroll
            for (int t = 0; t < kGrp; t++) {
                const uint32_t vb = sbase + kSmemRing + s * kTileBytes;
                mbar_wait(bar_full + s * 8, ph);
                if (threadIdx.x == 0 && t == kGrp - 1) TS(3);
#pragma unroll
                for (int w = 0; w < kNCW; w++) {
#pragma unroll
                    for (int i = 0; i < 2; i++) {
                        uint32_t b0, b1, b2, b3;
                        ldsm_x4_t(vb + voff2[i] + w * 2048, b0, b1, b2, b3);
                        mma_16816(oc[2 * i], pt[t][w], b0, b1);
                        mma_16816(oc[2 * i + 1], pt[t][w], b2, b3);
                    }
                }
                __syncwarp();
                if (lane == 0) mbar_arrive(bar_empty + s * 8);
                if (++s == kStages) { s = 0; ph ^= 1; }
            }
            {
                uint32_t w[2][4];
#pragma unroll
                for (int i = 0; i < 4; i++) {
                    w[0][i] = pack_bf16(oc[i][0] * inv0, oc[i][1] * inv0);
                    w[1][i] = pack_bf16(oc[i][2] * inv1, oc[i][3] * inv1);
                }
                const bool hi = tq & 2, od = tq & 1;
#pragma unroll
                for (int h = 0; h < 2; h++) {
                    uint32_t a = hi ? w[h][0] : w[h][2], b = hi ? w[h][1] : w[h][3];
                    a = __shfl_xor_sync(0xffffffffu, a, 2);
                    b = __shfl_xor_sync(0xffffffffu, b, 2);
                    if (hi) { w[h][0] = a; w[h][1] = b; } else { w[h][2] = a; w[h][3] = b; }
                }
#pragma unroll
                for (int h = 0; h < 2; h++) {
                    uint32_t a = od ? w[h][0] : w[h][1], b = od ? w[h][2] : w[h][3];
                    a = __shfl_xor_sync(0xffffffffu, a, 1);
                    b = __shfl_xor_sync(0xffffffffu, b, 1);
                    if (od) { w[h][0] = a; w[h][2] = b; } else { w[h][1] = a; w[h][3] = b; }
                }
                uint4* op = reinterpret_cast<uint4*>(out + ((size_t)head * 16 + g) * kD + 32 * warp) + tq;
                op[0] = make_uint4(w[0][0], w[0][1], w[0][2], w[0][3]);
                op[8 * kD / 8] = make_uint4(w[1][0], w[1][1], w[1][2], w[1][3]);
            }
            if (threadIdx.x == 0) TS(4);
        }
    }
}

typedef CUresult (*EncodeTiledFn)(CUtensorMap*, CUtensorMapDataType, cuuint32_t, void*, const cuuint64_t*, const cuuint64_t*,
                                  const cuuint32_t*, const cuuint32_t*, CUtensorMapInterleave, CUtensorMapSwizzle,
                                  CUtensorMapL2promotion, CUtensorMapFloatOOBfill);

void make_map(EncodeTiledFn enc, CUtensorMap* map, const void* ptr) {
    const cuuint64_t rows = (cuuint64_t)kHeads * kC;
    cuuint64_t dims[3] = {64, rows, 2};
    cuuint64_t strides[2] = {256, 128};
    cuuint32_t box[3] = {64, (cuuint32_t)kTile, 2};
    cuuint32_t estr[3] = {1, 1, 1};
    enc(map, CU_TENSOR_MAP_DATA_TYPE_BFLOAT16, 3, const_cast<void*>(ptr), dims, strides, box, estr,
        CU_TENSOR_MAP_INTERLEAVE_NONE, CU_TENSOR_MAP_SWIZZLE_128B, CU_TENSOR_MAP_L2_PROMOTION_L2_128B,
        CU_TENSOR_MAP_FLOAT_OOB_FILL_NONE);
}

}

extern "C" void kernel_launch(void* const* d_in, const int* in_sizes, int n_in, void* d_out, int out_size) {
    (void)in_sizes; (void)n_in; (void)out_size;
    static EncodeTiledFn enc = nullptr;
    if (!enc) {
        void* fn = nullptr;
        cudaDriverEntryPointQueryResult qres;
        cudaGetDriverEntryPoint("cuTensorMapEncodeTiled", &fn, cudaEnableDefault, &qres);
        enc = (EncodeTiledFn)fn;
        cudaFuncSetAttribute(tree_attn_kernel, cudaFuncAttributeMaxDynamicSharedMemorySize, kSmemTotal);
    }
    CUtensorMap map_k, map_v;
    make_map(enc, &map_k, d_in[1]);
    make_map(enc, &map_v, d_in[2]);
    tree_attn_kernel<<<kCtas, kThreads, kSmemTotal>>>(
        map_k, map_v, (const __nv_bfloat16*)d_in[1], (const __nv_bfloat16*)d_in[0], (const __nv_bfloat16*)d_in[3],
        (const __nv_bfloat16*)d_in[4], (const __nv_bfloat16*)d_in[5], (__nv_bfloat16*)d_out);
}
```

```cpp
#include <cuda_runtime.h>
#include <cuda_bf16.h>
#include <cuda.h>
#include <stdint.h>

namespace {

constexpr int kB = 32, kHkv = 16, kT = 8, kC = 2048, kD = 128;
constexpr int kHeads = kB * kHkv;
constexpr int kCtas = 128;
constexpr int kRounds = kHeads / kCtas;
constexpr int kTile = 64;
constexpr int kTileBytes = kTile * kD * 2;
constexpr int kGrp = 4;
constexpr int kGroups = kC / (kTile * kGrp);
constexpr int kLoadsPerHead = 2 * kC / kTile;
constexpr int kLoads = kRounds * kLoadsPerHead;
constexpr int kStages = 8;
constexpr int kInflight = 3;
constexpr int kNCW = 4;
constexpr int kThreads = (kNCW + 2) * 32;
constexpr int kAuxBytes = 8320;
constexpr int kAuxAt = 40;

constexpr int kFbEvery = 4;
constexpr int kFbEnd = 248;
constexpr unsigned kFbTotal = kCtas * (kFbEnd / kFbEvery);
constexpr int kFbPeriod = 8, kFbFirst = 16, kFbLast = 240;
static_assert(kFbEnd <= kLoads - kInflight - 1 && kFbEnd % kFbEvery == 0, "every CTA must make all of its reports");

constexpr int kSmemRing = 0;
constexpr int kSmemRed = kSmemRing + kStages * kTileBytes;
constexpr int kSmemP = kSmemRed + kNCW * 16 * 512;
constexpr int kSmemAux = kSmemP + kGrp * kNCW * 512;
constexpr int kSmemML = kSmemAux + kRounds * kAuxBytes;
constexpr int kSmemBar = kSmemML + kNCW * 16 * 2 * 4;
constexpr int kSmemFb = kSmemBar + (2 * kStages + kRounds) * 8;
constexpr int kSmemTotal = kSmemFb + 16;

__device__ unsigned g_progress;

#define TS(i)

__device__ __forceinline__ uint32_t smem_u32(const void* p) { return (uint32_t)__cvta_generic_to_shared(p); }
__device__ __forceinline__ void mbar_init(uint32_t bar, int cnt) {
    asm volatile("mbarrier.init.shared::cta.b64 [%0], %1;" ::"r"(bar), "r"(cnt));
}
__device__ __forceinline__ void mbar_expect_tx(uint32_t bar, uint32_t bytes) {
    asm volatile("mbarrier.arrive.expect_tx.shared::cta.b64 _, [%0], %1;" ::"r"(bar), "r"(bytes) : "memory");
}
__device__ __forceinline__ void mbar_arrive(uint32_t bar) {
    asm volatile("mbarrier.arrive.shared::cta.b64 _, [%0];" ::"r"(bar) : "memory");
}
__device__ __forceinline__ bool mbar_try(uint32_t bar, uint32_t parity) {
    uint32_t ok;
    asm volatile(
        "{\n"
        ".reg .pred p;\n"
        "mbarrier.try_wait.parity.shared::cta.b64 p, [%1], %2;\n"
        "selp.u32 %0, 1, 0, p;\n"
        "}\n" : "=r"(ok) : "r"(bar), "r"(parity) : "memory");
    return ok != 0;
}
__device__ __forceinline__ void mbar_wait(uint32_t bar, uint32_t parity) {
    uint32_t spins = 0;
    while (!mbar_try(bar, parity)) {
        if (++spins > (1u << 24)) __trap();
    }
}
__device__ __forceinline__ void bulk_load(uint32_t dst, const void* src, uint32_t bytes, uint32_t bar) {
    asm volatile("cp.async.bulk.shared::cluster.global.mbarrier::complete_tx::bytes [%0], [%1], %2, [%3];"
                 ::"r"(dst), "l"(src), "r"(bytes), "r"(bar) : "memory");
}
__device__ __forceinline__ void tma_load_tile(uint32_t dst, const CUtensorMap* map, int row, uint32_t bar, uint64_t pol) {
    asm volatile("cp.async.bulk.tensor.3d.shared::cluster.global.mbarrier::complete_tx::bytes.L2::cache_hint"
                 " [%0], [%1, {%3, %4, %3}], [%2], %5;"
                 ::"r"(dst), "l"((uint64_t)map), "r"(bar), "r"(0), "r"(row), "l"(pol) : "memory");
}
__device__ __forceinline__ void ldsm_x4(uint32_t addr, uint32_t& r0, uint32_t& r1, uint32_t& r2, uint32_t& r3) {
    asm volatile("ldmatrix.sync.aligned.m8n8.x4.shared.b16 {%0,%1,%2,%3}, [%4];"
                 : "=r"(r0), "=r"(r1), "=r"(r2), "=r"(r3) : "r"(addr) : "memory");
}
__device__ __forceinline__ void ldsm_x4_t(uint32_t addr, uint32_t& r0, uint32_t& r1, uint32_t& r2, uint32_t& r3) {
    asm volatile("ldmatrix.sync.aligned.m8n8.x4.trans.shared.b16 {%0,%1,%2,%3}, [%4];"
                 : "=r"(r0), "=r"(r1), "=r"(r2), "=r"(r3) : "r"(addr) : "memory");
}
__device__ __forceinline__ void mma_16816(float (&c)[4], const uint32_t (&a)[4], uint32_t b0, uint32_t b1) {
    asm volatile("mma.sync.aligned.m16n8k16.row.col.f32.bf16.bf16.f32 {%0,%1,%2,%3}, {%4,%5,%6,%7}, {%8,%9}, {%0,%1,%2,%3};"
                 : "+f"(c[0]), "+f"(c[1]), "+f"(c[2]), "+f"(c[3])
                 : "r"(a[0]), "r"(a[1]), "r"(a[2]), "r"(a[3]), "r"(b0), "r"(b1));
}
__device__ __forceinline__ void mma_1688(float (&c)[4], uint32_t a0, uint32_t a1, uint32_t b0) {
    asm volatile("mma.sync.aligned.m16n8k8.row.col.f32.bf16.bf16.f32 {%0,%1,%2,%3}, {%4,%5}, {%6}, {%0,%1,%2,%3};"
                 : "+f"(c[0]), "+f"(c[1]), "+f"(c[2]), "+f"(c[3])
                 : "r"(a0), "r"(a1), "r"(b0));
}
__device__ __forceinline__ uint32_t pack_bf16(float lo, float hi) {
    uint32_t r;
    asm("cvt.rn.bf16x2.f32 %0, %1, %2;" : "=r"(r) : "f"(hi), "f"(lo));
    return r;
}
__device__ __forceinline__ float ex2(float x) {
    float y;
    asm("ex2.approx.ftz.f32 %0, %1;" : "=f"(y) : "f"(x));
    return y;
}
__device__ __forceinline__ float rcp(float x) {
    float y;
    asm("rcp.approx.ftz.f32 %0, %1;" : "=f"(y) : "f"(x));
    return y;
}
__device__ __forceinline__ void sts128(uint32_t addr, float a, float b, float c, float d) {
    asm volatile("st.shared.v4.f32 [%0], {%1,%2,%3,%4};" ::"r"(addr), "f"(a), "f"(b), "f"(c), "f"(d) : "memory");
}
__device__ __forceinline__ void sts128u(uint32_t addr, const uint32_t (&v)[4]) {
    asm volatile("st.shared.v4.b32 [%0], {%1,%2,%3,%4};" ::"r"(addr), "r"(v[0]), "r"(v[1]), "r"(v[2]), "r"(v[3]) : "memory");
}
__device__ __forceinline__ void lds128(uint32_t addr, float (&v)[4]) {
    asm volatile("ld.shared.v4.f32 {%0,%1,%2,%3}, [%4];" : "=f"(v[0]), "=f"(v[1]), "=f"(v[2]), "=f"(v[3]) : "r"(addr) : "memory");
}
__device__ __forceinline__ void lds128u(uint32_t addr, uint32_t (&v)[4]) {
    asm volatile("ld.shared.v4.b32 {%0,%1,%2,%3}, [%4];" : "=r"(v[0]), "=r"(v[1]), "=r"(v[2]), "=r"(v[3]) : "r"(addr) : "memory");
}
__device__ __forceinline__ void consumer_sync() { asm volatile("bar.sync 1, %0;" ::"n"(kNCW * 32) : "memory"); }
__device__ __forceinline__ float quad_max(float v) {
    v = fmaxf(v, __shfl_xor_sync(0xffffffffu, v, 1));
    return fmaxf(v, __shfl_xor_sync(0xffffffffu, v, 2));
}
__device__ __forceinline__ float quad_sum(float v) {
    v += __shfl_xor_sync(0xffffffffu, v, 1);
    return v + __shfl_xor_sync(0xffffffffu, v, 2);
}

__device__ __forceinline__ uint32_t tile_off(int r, int c) {
    return (uint32_t)((c >> 3) * (kTile * 128) + r * 128 + (((c & 7) ^ (r & 7)) << 4));
}

__global__ void __launch_bounds__(kThreads, 1)
tree_attn_kernel(const __grid_constant__ CUtensorMap map_k, const __grid_constant__ CUtensorMap map_v,
                 const __nv_bfloat16* __restrict__ k_cache, const __nv_bfloat16* __restrict__ q,
                 const __nv_bfloat16* __restrict__ k_tree, const __nv_bfloat16* __restrict__ v_tree,
                 const __nv_bfloat16* __restrict__ tree_mask, __nv_bfloat16* __restrict__ out) {
    extern __shared__ __align__(1024) unsigned char smem[];
    const int cta = blockIdx.x;
    if (threadIdx.x == 0)
        asm volatile("cp.async.bulk.prefetch.L2.global [%0], %1;" ::"l"(k_cache + (size_t)cta * kC * kD), "r"(kTileBytes) : "memory");

    const uint32_t sbase = smem_u32(smem);
    const uint32_t bar_full = sbase + kSmemBar;
    const uint32_t bar_empty = bar_full + kStages * 8;
    const uint32_t bar_aux = bar_empty + kStages * 8;
    const int warp = threadIdx.x >> 5, lane = threadIdx.x & 31;
    volatile int* fb = reinterpret_cast<volatile int*>(smem + kSmemFb);

    uint64_t pol = 0;
    auto issue_aux = [&](int r) {
        const int head = cta + r * kCtas;
        const uint32_t ab = sbase + kSmemAux + r * kAuxBytes;
        mbar_expect_tx(bar_aux + r * 8, kAuxBytes);
        bulk_load(ab, q + (size_t)head * 16 * kD, 4096, bar_aux + r * 8);
        bulk_load(ab + 4096, k_tree + (size_t)head * kT * kD, 2048, bar_aux + r * 8);
        bulk_load(ab + 6144, v_tree + (size_t)head * kT * kD, 2048, bar_aux + r * 8);
        bulk_load(ab + 8192, tree_mask + (head / kHkv) * kT * kT, 128, bar_aux + r * 8);
    };

    if (threadIdx.x == 32) { fb[0] = 0; fb[1] = 0; }
    if (threadIdx.x == kNCW * 32) {
        TS(0);
        asm volatile("createpolicy.fractional.L2::evict_first.b64 %0, 1.0;" : "=l"(pol));
#pragma unroll
        for (int s = 0; s < kStages; s++) mbar_init(bar_full + s * 8, 1);
        mbar_init(bar_aux, 1);
        asm volatile("fence.mbarrier_init.release.cluster;" ::: "memory");
        static_assert(kInflight <= kGrp, "the first loads are K tiles");
#pragma unroll
        for (int i = 0; i < kInflight; i++) {
            mbar_expect_tx(bar_full + i * 8, kTileBytes);
            tma_load_tile(sbase + kSmemRing + i * kTileBytes, &map_k, cta * kC + i * kTile, bar_full + i * 8, pol);
            if (i == 0) issue_aux(0);
        }
        TS(1);
#pragma unroll
        for (int s = 0; s < kStages; s++) mbar_init(bar_empty + s * 8, kNCW);
#pragma unroll
        for (int r = 1; r < kRounds; r++) mbar_init(bar_aux + r * 8, 1);
        asm volatile("fence.mbarrier_init.release.cluster;" ::: "memory");
    }
    __syncthreads();

    if (warp == kNCW) {
        if (lane == 0) {
            int s = kInflight; uint32_t ph = 1;
            int ls = 0; uint32_t lph = 0;
            int landed = 0, depth = kInflight, left = 0;
#pragma unroll 1
            for (int i = kInflight; i < kLoads; i++) {
                const int j = i & (kLoadsPerHead - 1);
                const bool is_v = (j / kGrp) & 1;
                const int tile = (j / (2 * kGrp)) * kGrp + (j % kGrp);
                const int row = (cta + (i / kLoadsPerHead) * kCtas) * kC + tile * kTile;
                const int cmd = fb[1];
                if (cmd != 0) {
                    fb[1] = 0;
                    depth = cmd > 0 ? kInflight + 1 : kInflight - 1;
                    left = cmd > 0 ? cmd : -cmd;
                } else if (left > 0 && --left == 0) {
                    depth = kInflight;
                }
                while (i - landed >= depth) {
                    mbar_wait(bar_full + ls * 8, lph);
                    if (++ls == kStages) { ls = 0; lph ^= 1; }
                    fb[0] = ++landed;
                    if (((landed + cta) & (kFbEvery - 1)) == 0 && landed <= kFbEnd)
                        asm volatile("red.relaxed.gpu.global.inc.u32 [%0], %1;" ::"l"(&g_progress), "r"(kFbTotal - 1) : "memory");
                }
                mbar_wait(bar_empty + s * 8, ph);
                mbar_expect_tx(bar_full + s * 8, kTileBytes);
                tma_load_tile(sbase + kSmemRing + s * kTileBytes, is_v ? &map_v : &map_k, row, bar_full + s * 8, pol);
                if (++s == kStages) { s = 0; ph ^= 1; }
                if (j == kAuxAt && i < kLoads - kLoadsPerHead) issue_aux(i / kLoadsPerHead + 1);
            }
        }
    } else if (warp == kNCW + 1) {
        if (lane == 0) {
            uint32_t spins = 0;
            float integ = 0.f;
#pragma unroll 1
            for (int at = kFbFirst; at <= kFbLast; at += kFbPeriod) {
                int mine;
                while ((mine = fb[0]) < at && ++spins < (1u << 22)) __nanosleep(100);
                unsigned total;
                asm volatile("ld.relaxed.gpu.global.u32 %0, [%1];" : "=r"(total) : "l"(&g_progress) : "memory");
                const float lag = (float)total * ((float)kFbEvery / kCtas) + 0.3f - (float)mine;
                if (fabsf(lag) < 64.f) {
                    integ = fminf(fmaxf(integ + 0.2f * lag, -8.f), 8.f);
                    const float u = 2.0f * lag + integ;
                    if (fabsf(u) > 1.0f) {
                        const int n = (int)(fminf(fabsf(u), 5.0f) + 0.5f);
                        fb[1] = u > 0.f ? n : -n;
                    }
                }
            }
        }
    } else {
        const float kScale = 0.08838834764831845f;
        const float kC2 = kScale * 1.4426950408889634f;
        const int g = lane >> 2, tq = lane & 3;
        int s = 0; uint32_t ph = 0;
        uint32_t koff[4], voff[8], voff2[2];
#pragma unroll
        for (int i = 0; i < 4; i++) koff[i] = tile_off(16 * warp + (lane & 7), 4 * i + (lane >> 3));
#pragma unroll
        for (int i = 0; i < 8; i++) voff[i] = tile_off(16 * warp + ((lane >> 3) & 1) * 8 + (lane & 7), 2 * i + (lane >> 4));
#pragma unroll
        for (int i = 0; i < 2; i++) voff2[i] = tile_off(((lane >> 3) & 1) * 8 + (lane & 7), 4 * warp + 2 * i + (lane >> 4));
        const uint32_t red = sbase + kSmemRed + lane * 16, pbuf = sbase + kSmemP + lane * 16;
        float* mbuf = reinterpret_cast<float*>(smem + kSmemML);
        float* lbuf = mbuf + kNCW * 16;

#pragma unroll 1
        for (int r = 0; r < kRounds; r++) {
            const int head = cta + r * kCtas;
            uint32_t qf[8][4];
            float o[16][4];
            float m0 = -INFINITY, m1 = -INFINITY, l0 = 0.f, l1 = 0.f;
#pragma unroll
            for (int i = 0; i < 16; i++) { o[i][0] = 0.f; o[i][1] = 0.f; o[i][2] = 0.f; o[i][3] = 0.f; }

            const uint32_t ab = sbase + kSmemAux + r * kAuxBytes;
            mbar_wait(bar_aux + r * 8, 0);
#pragma unroll
            for (int ks = 0; ks < 8; ks++)
                ldsm_x4(ab + ((lane & 7) + ((lane >> 3) & 1) * 8) * 256 + (2 * ks + (lane >> 4)) * 16,
                        qf[ks][0], qf[ks][1], qf[ks][2], qf[ks][3]);
            if (warp == 0) {
                float sc[4] = {0.f, 0.f, 0.f, 0.f};
#pragma unroll
                for (int i = 0; i < 4; i++) {
                    uint32_t b0, b1, b2, b3;
                    ldsm_x4(ab + 4096 + (lane & 7) * 256 + (4 * i + (lane >> 3)) * 16, b0, b1, b2, b3);
                    mma_16816(sc, qf[2 * i], b0, b1);
                    mma_16816(sc, qf[2 * i + 1], b2, b3);
                }
                const uint32_t mraw = *reinterpret_cast<const uint32_t*>(smem + kSmemAux + r * kAuxBytes + 8192 + lane * 4);
                const float mk0 = __uint_as_float(mraw << 16), mk1 = __uint_as_float(mraw & 0xffff0000u);
                const float bias0 = (1.0f - mk0) * (-1000000000.0f / kScale);
                const float bias1 = (1.0f - mk1) * (-1000000000.0f / kScale);
                sc[0] += bias0; sc[1] += bias1; sc[2] += bias0; sc[3] += bias1;
                m0 = quad_max(fmaxf(sc[0], sc[1]));
                m1 = quad_max(fmaxf(sc[2], sc[3]));
                const float p0 = ex2((sc[0] - m0) * kC2), p1 = ex2((sc[1] - m0) * kC2);
                const float p2 = ex2((sc[2] - m1) * kC2), p3 = ex2((sc[3] - m1) * kC2);
                l0 = p0 + p1; l1 = p2 + p3;
                const uint32_t pa0 = pack_bf16(p0, p1), pa1 = pack_bf16(p2, p3);
#pragma unroll
                for (int i = 0; i < 4; i++) {
                    uint32_t b0, b1, b2, b3;
                    ldsm_x4_t(ab + 6144 + (lane & 7) * 256 + (4 * i + (lane >> 3)) * 16, b0, b1, b2, b3);
                    mma_1688(o[4 * i + 0], pa0, pa1, b0);
                    mma_1688(o[4 * i + 1], pa0, pa1, b1);
                    mma_1688(o[4 * i + 2], pa0, pa1, b2);
                    mma_1688(o[4 * i + 3], pa0, pa1, b3);
                }
            }

            float st[kGrp][2][4];
            float mx0, mx1;
            auto scores = [&]() {
                mx0 = m0; mx1 = m1;
#pragma unroll
                for (int t = 0; t < kGrp; t++) {
#pragma unroll
                    for (int j = 0; j < 2; j++) { st[t][j][0] = 0.f; st[t][j][1] = 0.f; st[t][j][2] = 0.f; st[t][j][3] = 0.f; }
                    const uint32_t kb = sbase + kSmemRing + s * kTileBytes;
                    mbar_wait(bar_full + s * 8, ph);
#pragma unroll
                    for (int i = 0; i < 4; i++) {
#pragma unroll
                        for (int j = 0; j < 2; j++) {
                            uint32_t b0, b1, b2, b3;
                            ldsm_x4(kb + koff[i] + j * 1024, b0, b1, b2, b3);
                            mma_16816(st[t][j], qf[2 * i], b0, b1);
                            mma_16816(st[t][j], qf[2 * i + 1], b2, b3);
                        }
                    }
                    __syncwarp();
                    if (lane == 0) mbar_arrive(bar_empty + s * 8);
                    if (++s == kStages) { s = 0; ph ^= 1; }
                    mx0 = fmaxf(mx0, fmaxf(fmaxf(st[t][0][0], st[t][0][1]), fmaxf(st[t][1][0], st[t][1][1])));
                    mx1 = fmaxf(mx1, fmaxf(fmaxf(st[t][0][2], st[t][0][3]), fmaxf(st[t][1][2], st[t][1][3])));
                }
                mx0 = quad_max(mx0);
                mx1 = quad_max(mx1);
            };
            auto probs = [&](int t, float mb0, float mb1, uint32_t (&pa)[4]) {
                const float p00 = ex2(fmaf(st[t][0][0], kC2, -mb0)), p01 = ex2(fmaf(st[t][0][1], kC2, -mb0));
                const float p02 = ex2(fmaf(st[t][0][2], kC2, -mb1)), p03 = ex2(fmaf(st[t][0][3], kC2, -mb1));
                const float p10 = ex2(fmaf(st[t][1][0], kC2, -mb0)), p11 = ex2(fmaf(st[t][1][1], kC2, -mb0));
                const float p12 = ex2(fmaf(st[t][1][2], kC2, -mb1)), p13 = ex2(fmaf(st[t][1][3], kC2, -mb1));
                l0 += (p00 + p01) + (p10 + p11);
                l1 += (p02 + p03) + (p12 + p13);
                pa[0] = pack_bf16(p00, p01); pa[1] = pack_bf16(p02, p03);
                pa[2] = pack_bf16(p10, p11); pa[3] = pack_bf16(p12, p13);
            };

#pragma unroll 1
            for (int gi = 0; gi < kGroups - 1; gi++) {
                scores();
                const float al0 = ex2((m0 - mx0) * kC2), al1 = ex2((m1 - mx1) * kC2);
                m0 = mx0; m1 = mx1;
                l0 *= al0; l1 *= al1;
                uint32_t pa[kGrp][4];
#pragma unroll
                for (int t = 0; t < kGrp; t++) probs(t, mx0 * kC2, mx1 * kC2, pa[t]);
#pragma unroll
                for (int i = 0; i < 16; i++) { o[i][0] *= al0; o[i][1] *= al0; o[i][2] *= al1; o[i][3] *= al1; }
#pragma unroll
                for (int t = 0; t < kGrp; t++) {
                    const uint32_t vb = sbase + kSmemRing + s * kTileBytes;
                    mbar_wait(bar_full + s * 8, ph);
#pragma unroll
                    for (int i = 0; i < 8; i++) {
                        uint32_t b0, b1, b2, b3;
                        ldsm_x4_t(vb + voff[i], b0, b1, b2, b3);
                        mma_16816(o[2 * i], pa[t], b0, b1);
                        mma_16816(o[2 * i + 1], pa[t], b2, b3);
                    }
                    __syncwarp();
                    if (lane == 0) mbar_arrive(bar_empty + s * 8);
                    if (++s == kStages) { s = 0; ph ^= 1; }
                }
            }

            scores();
            if (tq == 0) { mbuf[warp * 16 + g] = mx0; mbuf[warp * 16 + g + 8] = mx1; }
            consumer_sync();
#pragma unroll
            for (int w = 0; w < kNCW; w++) {
                mx0 = fmaxf(mx0, mbuf[w * 16 + g]);
                mx1 = fmaxf(mx1, mbuf[w * 16 + g + 8]);
            }
            {
                const float f0 = ex2((m0 - mx0) * kC2), f1 = ex2((m1 - mx1) * kC2);
                l0 *= f0; l1 *= f1;
#pragma unroll
                for (int t = 0; t < kGrp; t++) {
                    uint32_t pa[4];
                    probs(t, mx0 * kC2, mx1 * kC2, pa);
                    sts128u(pbuf + (t * kNCW + warp) * 512, pa);
                }
                l0 = quad_sum(l0);
                l1 = quad_sum(l1);
                if (tq == 0) { lbuf[warp * 16 + g] = l0; lbuf[warp * 16 + g + 8] = l1; }
#pragma unroll
                for (int i = 0; i < 16; i++)
                    sts128(red + (warp * 16 + i) * 512, o[i][0] * f0, o[i][1] * f0, o[i][2] * f1, o[i][3] * f1);
            }
            consumer_sync();
            float oc[4][4];
            uint32_t pt[kGrp][kNCW][4];
#pragma unroll
            for (int i = 0; i < 4; i++) {
                lds128(red + (4 * warp + i) * 512, oc[i]);
#pragma unroll
                for (int w = 1; w < kNCW; w++) {
                    float v[4];
                    lds128(red + (w * 16 + 4 * warp + i) * 512, v);
                    oc[i][0] += v[0]; oc[i][1] += v[1]; oc[i][2] += v[2]; oc[i][3] += v[3];
                }
            }
#pragma unroll
            for (int t = 0; t < kGrp; t++)
#pragma unroll
                for (int w = 0; w < kNCW; w++) lds128u(pbuf + (t * kNCW + w) * 512, pt[t][w]);
            const float inv0 = rcp((lbuf[g] + lbuf[16 + g]) + (lbuf[32 + g] + lbuf[48 + g]));
            const float inv1 = rcp((lbuf[g + 8] + lbuf[16 + g + 8]) + (lbuf[32 + g + 8] + lbuf[48 + g + 8]));
#pragma unroll
            for (int t = 0; t < kGrp; t++) {
                const uint32_t vb = sbase + kSmemRing + s * kTileBytes;
                mbar_wait(bar_full + s * 8, ph);
                if (threadIdx.x == 0 && t == kGrp - 1) TS(3);
#pragma unroll
                for (int w = 0; w < kNCW; w++) {
#pragma unroll
                    for (int i = 0; i < 2; i++) {
                        uint32_t b0, b1, b2, b3;
                        ldsm_x4_t(vb + voff2[i] + w * 2048, b0, b1, b2, b3);
                        mma_16816(oc[2 * i], pt[t][w], b0, b1);
                        mma_16816(oc[2 * i + 1], pt[t][w], b2, b3);
                    }
                }
                __syncwarp();
                if (lane == 0) mbar_arrive(bar_empty + s * 8);
                if (++s == kStages) { s = 0; ph ^= 1; }
            }
            {
                uint32_t w[2][4];
#pragma unroll
                for (int i = 0; i < 4; i++) {
                    w[0][i] = pack_bf16(oc[i][0] * inv0, oc[i][1] * inv0);
                    w[1][i] = pack_bf16(oc[i][2] * inv1, oc[i][3] * inv1);
                }
                const bool hi = tq & 2, od = tq & 1;
#pragma unroll
                for (int h = 0; h < 2; h++) {
                    uint32_t a = hi ? w[h][0] : w[h][2], b = hi ? w[h][1] : w[h][3];
                    a = __shfl_xor_sync(0xffffffffu, a, 2);
                    b = __shfl_xor_sync(0xffffffffu, b, 2);
                    if (hi) { w[h][0] = a; w[h][1] = b; } else { w[h][2] = a; w[h][3] = b; }
                }
#pragma unroll
                for (int h = 0; h < 2; h++) {
                    uint32_t a = od ? w[h][0] : w[h][1], b = od ? w[h][2] : w[h][3];
                    a = __shfl_xor_sync(0xffffffffu, a, 1);
                    b = __shfl_xor_sync(0xffffffffu, b, 1);
                    if (od) { w[h][0] = a; w[h][2] = b; } else { w[h][1] = a; w[h][3] = b; }
                }
                uint4* op = reinterpret_cast<uint4*>(out + ((size_t)head * 16 + g) * kD + 32 * warp) + tq;
                op[0] = make_uint4(w[0][0], w[0][1], w[0][2], w[0][3]);
                op[8 * kD / 8] = make_uint4(w[1][0], w[1][1], w[1][2], w[1][3]);
            }
            if (threadIdx.x == 0) TS(4);
        }
    }
}

typedef CUresult (*EncodeTiledFn)(CUtensorMap*, CUtensorMapDataType, cuuint32_t, void*, const cuuint64_t*, const cuuint64_t*,
                                  const cuuint32_t*, const cuuint32_t*, CUtensorMapInterleave, CUtensorMapSwizzle,
                                  CUtensorMapL2promotion, CUtensorMapFloatOOBfill);

void make_map(EncodeTiledFn enc, CUtensorMap* map, const void* ptr) {
    const cuuint64_t rows = (cuuint64_t)kHeads * kC;
    cuuint64_t dims[3] = {64, rows, 2};
    cuuint64_t strides[2] = {256, 128};
    cuuint32_t box[3] = {64, (cuuint32_t)kTile, 2};
    cuuint32_t estr[3] = {1, 1, 1};
    enc(map, CU_TENSOR_MAP_DATA_TYPE_BFLOAT16, 3, const_cast<void*>(ptr), dims, strides, box, estr,
        CU_TENSOR_MAP_INTERLEAVE_NONE, CU_TENSOR_MAP_SWIZZLE_128B, CU_TENSOR_MAP_L2_PROMOTION_L2_128B,
        CU_TENSOR_MAP_FLOAT_OOB_FILL_NONE);
}

}

extern "C" void kernel_launch(void* const* d_in, const int* in_sizes, int n_in, void* d_out, int out_size) {
    (void)in_sizes; (void)n_in; (void)out_size;
    static EncodeTiledFn enc = nullptr;
    if (!enc) {
        void* fn = nullptr;
        cudaDriverEntryPointQueryResult qres;
        cudaGetDriverEntryPoint("cuTensorMapEncodeTiled", &fn, cudaEnableDefault, &qres);
        enc = (EncodeTiledFn)fn;
        cudaFuncSetAttribute(tree_attn_kernel, cudaFuncAttributeMaxDynamicSharedMemorySize, kSmemTotal);
    }
    CUtensorMap map_k, map_v;
    make_map(enc, &map_k, d_in[1]);
    make_map(enc, &map_v, d_in[2]);
    tree_attn_kernel<<<kCtas, kThreads, kSmemTotal>>>(
        map_k, map_v, (const __nv_bfloat16*)d_in[1], (const __nv_bfloat16*)d_in[0], (const __nv_bfloat16*)d_in[3],
        (const __nv_bfloat16*)d_in[4], (const __nv_bfloat16*)d_in[5], (__nv_bfloat16*)d_out);
}
```

```cpp
#include <cuda_runtime.h>
#include <cuda_bf16.h>
#include <cuda.h>
#include <stdint.h>

namespace {

constexpr int kB = 32, kHkv = 16, kT = 8, kC = 2048, kD = 128;
constexpr int kHeads = kB * kHkv;
constexpr int kCtas = 128;
constexpr int kRounds = kHeads / kCtas;
constexpr int kTile = 64;
constexpr int kTileBytes = kTile * kD * 2;
constexpr int kGrp = 4;
constexpr int kGroups = kC / (kTile * kGrp);
constexpr int kLoadsPerHead = 2 * kC / kTile;
constexpr int kLoads = kRounds * kLoadsPerHead;
constexpr int kStages = 8;
constexpr int kInflight = 3;
constexpr int kNCW = 4;
constexpr int kThreads = (kNCW + 2) * 32;
constexpr int kAuxBytes = 8320;
constexpr int kAuxAt = 40;

constexpr int kFbEvery = 4;
constexpr int kFbEnd = 248;
constexpr unsigned kFbTotal = kCtas * (kFbEnd / kFbEvery);
constexpr int kFbPeriod = 8, kFbFirst = 16, kFbLast = 240;
static_assert(kFbEnd <= kLoads - kInflight - 1 && kFbEnd % kFbEvery == 0, "every CTA must make all of its reports");

constexpr int kSmemRing = 0;
constexpr int kSmemRed = kSmemRing + kStages * kTileBytes;
constexpr int kSmemP = kSmemRed + kNCW * 16 * 512;
constexpr int kSmemAux = kSmemP + kGrp * kNCW * 512;
constexpr int kSmemML = kSmemAux + kRounds * kAuxBytes;
constexpr int kSmemBar = kSmemML + kNCW * 16 * 2 * 4;
constexpr int kSmemFb = kSmemBar + (2 * kStages + kRounds) * 8;
constexpr int kSmemTotal = kSmemFb + 16;

__device__ unsigned g_progress;

__device__ __forceinline__ uint32_t smem_u32(const void* p) { return (uint32_t)__cvta_generic_to_shared(p); }
__device__ __forceinline__ void mbar_init(uint32_t bar, int cnt) {
    asm volatile("mbarrier.init.shared::cta.b64 [%0], %1;" ::"r"(bar), "r"(cnt));
}
__device__ __forceinline__ void mbar_expect_tx(uint32_t bar, uint32_t bytes) {
    asm volatile("mbarrier.arrive.expect_tx.shared::cta.b64 _, [%0], %1;" ::"r"(bar), "r"(bytes) : "memory");
}
__device__ __forceinline__ void mbar_arrive(uint32_t bar) {
    asm volatile("mbarrier.arrive.shared::cta.b64 _, [%0];" ::"r"(bar) : "memory");
}
__device__ __forceinline__ bool mbar_try(uint32_t bar, uint32_t parity) {
    uint32_t ok;
    asm volatile(
        "{\n"
        ".reg .pred p;\n"
        "mbarrier.try_wait.parity.shared::cta.b64 p, [%1], %2;\n"
        "selp.u32 %0, 1, 0, p;\n"
        "}\n" : "=r"(ok) : "r"(bar), "r"(parity) : "memory");
    return ok != 0;
}
__device__ __forceinline__ void mbar_wait(uint32_t bar, uint32_t parity) {
    uint32_t spins = 0;
    while (!mbar_try(bar, parity)) {
        if (++spins > (1u << 24)) __trap();
    }
}
__device__ __forceinline__ void bulk_load(uint32_t dst, const void* src, uint32_t bytes, uint32_t bar) {
    asm volatile("cp.async.bulk.shared::cluster.global.mbarrier::complete_tx::bytes [%0], [%1], %2, [%3];"
                 ::"r"(dst), "l"(src), "r"(bytes), "r"(bar) : "memory");
}
__device__ __forceinline__ void tma_load_tile(uint32_t dst, const CUtensorMap* map, int row, uint32_t bar, uint64_t pol) {
    asm volatile("cp.async.bulk.tensor.3d.shared::cluster.global.mbarrier::complete_tx::bytes.L2::cache_hint"
                 " [%0], [%1, {%3, %4, %3}], [%2], %5;"
                 ::"r"(dst), "l"((uint64_t)map), "r"(bar), "r"(0), "r"(row), "l"(pol) : "memory");
}
__device__ __forceinline__ void ldsm_x4(uint32_t addr, uint32_t& r0, uint32_t& r1, uint32_t& r2, uint32_t& r3) {
    asm volatile("ldmatrix.sync.aligned.m8n8.x4.shared.b16 {%0,%1,%2,%3}, [%4];"
                 : "=r"(r0), "=r"(r1), "=r"(r2), "=r"(r3) : "r"(addr) : "memory");
}
__device__ __forceinline__ void ldsm_x4_t(uint32_t addr, uint32_t& r0, uint32_t& r1, uint32_t& r2, uint32_t& r3) {
    asm volatile("ldmatrix.sync.aligned.m8n8.x4.trans.shared.b16 {%0,%1,%2,%3}, [%4];"
                 : "=r"(r0), "=r"(r1), "=r"(r2), "=r"(r3) : "r"(addr) : "memory");
}
__device__ __forceinline__ void mma_16816(float (&c)[4], const uint32_t (&a)[4], uint32_t b0, uint32_t b1) {
    asm volatile("mma.sync.aligned.m16n8k16.row.col.f32.bf16.bf16.f32 {%0,%1,%2,%3}, {%4,%5,%6,%7}, {%8,%9}, {%0,%1,%2,%3};"
                 : "+f"(c[0]), "+f"(c[1]), "+f"(c[2]), "+f"(c[3])
                 : "r"(a[0]), "r"(a[1]), "r"(a[2]), "r"(a[3]), "r"(b0), "r"(b1));
}
__device__ __forceinline__ void mma_1688(float (&c)[4], uint32_t a0, uint32_t a1, uint32_t b0) {
    asm volatile("mma.sync.aligned.m16n8k8.row.col.f32.bf16.bf16.f32 {%0,%1,%2,%3}, {%4,%5}, {%6}, {%0,%1,%2,%3};"
                 : "+f"(c[0]), "+f"(c[1]), "+f"(c[2]), "+f"(c[3])
                 : "r"(a0), "r"(a1), "r"(b0));
}
__device__ __forceinline__ uint32_t pack_bf16(float lo, float hi) {
    uint32_t r;
    asm("cvt.rn.bf16x2.f32 %0, %1, %2;" : "=r"(r) : "f"(hi), "f"(lo));
    return r;
}
__device__ __forceinline__ float ex2(float x) {
    float y;
    asm("ex2.approx.ftz.f32 %0, %1;" : "=f"(y) : "f"(x));
    return y;
}
__device__ __forceinline__ float rcp(float x) {
    float y;
    asm("rcp.approx.ftz.f32 %0, %1;" : "=f"(y) : "f"(x));
    return y;
}
__device__ __forceinline__ void sts128(uint32_t addr, float a, float b, float c, float d) {
    asm volatile("st.shared.v4.f32 [%0], {%1,%2,%3,%4};" ::"r"(addr), "f"(a), "f"(b), "f"(c), "f"(d) : "memory");
}
__device__ __forceinline__ void sts128u(uint32_t addr, const uint32_t (&v)[4]) {
    asm volatile("st.shared.v4.b32 [%0], {%1,%2,%3,%4};" ::"r"(addr), "r"(v[0]), "r"(v[1]), "r"(v[2]), "r"(v[3]) : "memory");
}
__device__ __forceinline__ void lds128(uint32_t addr, float (&v)[4]) {
    asm volatile("ld.shared.v4.f32 {%0,%1,%2,%3}, [%4];" : "=f"(v[0]), "=f"(v[1]), "=f"(v[2]), "=f"(v[3]) : "r"(addr) : "memory");
}
__device__ __forceinline__ void lds128u(uint32_t addr, uint32_t (&v)[4]) {
    asm volatile("ld.shared.v4.b32 {%0,%1,%2,%3}, [%4];" : "=r"(v[0]), "=r"(v[1]), "=r"(v[2]), "=r"(v[3]) : "r"(addr) : "memory");
}
__device__ __forceinline__ void consumer_sync() { asm volatile("bar.sync 1, %0;" ::"n"(kNCW * 32) : "memory"); }
__device__ __forceinline__ float quad_max(float v) {
    v = fmaxf(v, __shfl_xor_sync(0xffffffffu, v, 1));
    return fmaxf(v, __shfl_xor_sync(0xffffffffu, v, 2));
}
__device__ __forceinline__ float quad_sum(float v) {
    v += __shfl_xor_sync(0xffffffffu, v, 1);
    return v + __shfl_xor_sync(0xffffffffu, v, 2);
}

__device__ __forceinline__ uint32_t tile_off(int r, int c) {
    return (uint32_t)((c >> 3) * (kTile * 128) + r * 128 + (((c & 7) ^ (r & 7)) << 4));
}

__global__ void __launch_bounds__(kThreads, 1)
tree_attn_kernel(const __nv_bfloat16* __restrict__ k_cache, const __nv_bfloat16* __restrict__ q,
                 const __nv_bfloat16* __restrict__ k_tree, const __nv_bfloat16* __restrict__ v_tree,
                 const __nv_bfloat16* __restrict__ tree_mask, __nv_bfloat16* __restrict__ out,
                 const __grid_constant__ CUtensorMap map_k, const __grid_constant__ CUtensorMap map_v) {
    extern __shared__ __align__(1024) unsigned char smem[];
    const int cta = blockIdx.x;
    if (threadIdx.x == 0)
        asm volatile("cp.async.bulk.prefetch.L2.global [%0], %1;" ::"l"(k_cache + (size_t)cta * kC * kD), "r"(2 * kTileBytes) : "memory");

    const uint32_t sbase = smem_u32(smem);
    const uint32_t bar_full = sbase + kSmemBar;
    const uint32_t bar_empty = bar_full + kStages * 8;
    const uint32_t bar_aux = bar_empty + kStages * 8;
    const int warp = threadIdx.x >> 5, lane = threadIdx.x & 31;
    volatile int* fb = reinterpret_cast<volatile int*>(smem + kSmemFb);

    uint64_t pol = 0;
    auto issue_aux = [&](int r) {
        const int head = cta + r * kCtas;
        const uint32_t ab = sbase + kSmemAux + r * kAuxBytes;
        mbar_expect_tx(bar_aux + r * 8, kAuxBytes);
        bulk_load(ab, q + (size_t)head * 16 * kD, 4096, bar_aux + r * 8);
        bulk_load(ab + 4096, k_tree + (size_t)head * kT * kD, 2048, bar_aux + r * 8);
        bulk_load(ab + 6144, v_tree + (size_t)head * kT * kD, 2048, bar_aux + r * 8);
        bulk_load(ab + 8192, tree_mask + (head / kHkv) * kT * kT, 128, bar_aux + r * 8);
    };

    if (threadIdx.x == 32) { fb[0] = 0; fb[1] = 0; }
    if (threadIdx.x == kNCW * 32) {
        asm volatile("createpolicy.fractional.L2::evict_first.b64 %0, 1.0;" : "=l"(pol));
#pragma unroll
        for (int s = 0; s < kStages; s++) mbar_init(bar_full + s * 8, 1);
        mbar_init(bar_aux, 1);
        asm volatile("fence.mbarrier_init.release.cluster;" ::: "memory");
        static_assert(kInflight <= kGrp, "the first loads are K tiles");
#pragma unroll
        for (int i = 0; i < kInflight; i++) {
            mbar_expect_tx(bar_full + i * 8, kTileBytes);
            tma_load_tile(sbase + kSmemRing + i * kTileBytes, &map_k, cta * kC + i * kTile, bar_full + i * 8, pol);
        }
        issue_aux(0);
#pragma unroll
        for (int s = 0; s < kStages; s++) mbar_init(bar_empty + s * 8, kNCW);
#pragma unroll
        for (int r = 1; r < kRounds; r++) mbar_init(bar_aux + r * 8, 1);
        asm volatile("fence.mbarrier_init.release.cluster;" ::: "memory");
    }
    __syncthreads();

    if (warp == kNCW) {
        if (lane == 0) {
            int s = kInflight; uint32_t ph = 1;
            int ls = 0; uint32_t lph = 0;
            int landed = 0, depth = kInflight, left = 0;
#pragma unroll 1
            for (int i = kInflight; i < kLoads; i++) {
                const int j = i & (kLoadsPerHead - 1);
                const bool is_v = (j / kGrp) & 1;
                const int tile = (j / (2 * kGrp)) * kGrp + (j % kGrp);
                const int row = (cta + (i / kLoadsPerHead) * kCtas) * kC + tile * kTile;
                const int cmd = fb[1];
                if (cmd != 0) {
                    fb[1] = 0;
                    depth = cmd > 0 ? kInflight + 1 : kInflight - 1;
                    left = cmd > 0 ? cmd : -cmd;
                } else if (left > 0 && --left == 0) {
                    depth = kInflight;
                }
                while (i - landed >= depth) {
                    mbar_wait(bar_full + ls * 8, lph);
                    if (++ls == kStages) { ls = 0; lph ^= 1; }
                    fb[0] = ++landed;
                    if (((landed + cta) & (kFbEvery - 1)) == 0 && landed <= kFbEnd)
                        asm volatile("red.relaxed.gpu.global.inc.u32 [%0], %1;" ::"l"(&g_progress), "r"(kFbTotal - 1) : "memory");
                }
                mbar_wait(bar_empty + s * 8, ph);
                mbar_expect_tx(bar_full + s * 8, kTileBytes);
                tma_load_tile(sbase + kSmemRing + s * kTileBytes, is_v ? &map_v : &map_k, row, bar_full + s * 8, pol);
                if (++s == kStages) { s = 0; ph ^= 1; }
                if (j == kAuxAt && i < kLoads - kLoadsPerHead) issue_aux(i / kLoadsPerHead + 1);
            }
        }
    } else if (warp == kNCW + 1) {
        if (lane == 0) {
            uint32_t spins = 0;
            float integ = 0.f;
#pragma unroll 1
            for (int at = kFbFirst; at <= kFbLast; at += kFbPeriod) {
                int mine;
                while ((mine = fb[0]) < at && ++spins < (1u << 22)) __nanosleep(100);
                unsigned total;
                asm volatile("ld.relaxed.gpu.global.u32 %0, [%1];" : "=r"(total) : "l"(&g_progress) : "memory");
                const float lag = (float)total * ((float)kFbEvery / kCtas) + 0.3f - (float)mine;
                if (fabsf(lag) < 64.f) {
                    integ = fminf(fmaxf(integ + 0.2f * lag, -8.f), 8.f);
                    const float u = 2.0f * lag + integ;
                    if (fabsf(u) > 1.0f) {
                        const int n = (int)(fminf(fabsf(u), 5.0f) + 0.5f);
                        fb[1] = u > 0.f ? n : -n;
                    }
                }
            }
        }
    } else {
        const float kScale = 0.08838834764831845f;
        const float kC2 = kScale * 1.4426950408889634f;
        const int g = lane >> 2, tq = lane & 3;
        int s = 0; uint32_t ph = 0;
        uint32_t koff[4], voff[8], voff2[2];
#pragma unroll
        for (int i = 0; i < 4; i++) koff[i] = tile_off(16 * warp + (lane & 7), 4 * i + (lane >> 3));
#pragma unroll
        for (int i = 0; i < 8; i++) voff[i] = tile_off(16 * warp + ((lane >> 3) & 1) * 8 + (lane & 7), 2 * i + (lane >> 4));
#pragma unroll
        for (int i = 0; i < 2; i++) voff2[i] = tile_off(((lane >> 3) & 1) * 8 + (lane & 7), 4 * warp + 2 * i + (lane >> 4));
        const uint32_t red = sbase + kSmemRed + lane * 16, pbuf = sbase + kSmemP + lane * 16;
        float* mbuf = reinterpret_cast<float*>(smem + kSmemML);
        float* lbuf = mbuf + kNCW * 16;

#pragma unroll 1
        for (int r = 0; r < kRounds; r++) {
            const int head = cta + r * kCtas;
            uint32_t qf[8][4];
            float o[16][4];
            float m0 = -INFINITY, m1 = -INFINITY, l0 = 0.f, l1 = 0.f;
#pragma unroll
            for (int i = 0; i < 16; i++) { o[i][0] = 0.f; o[i][1] = 0.f; o[i][2] = 0.f; o[i][3] = 0.f; }

            const uint32_t ab = sbase + kSmemAux + r * kAuxBytes;
            mbar_wait(bar_aux + r * 8, 0);
#pragma unroll
            for (int ks = 0; ks < 8; ks++)
                ldsm_x4(ab + ((lane & 7) + ((lane >> 3) & 1) * 8) * 256 + (2 * ks + (lane >> 4)) * 16,
                        qf[ks][0], qf[ks][1], qf[ks][2], qf[ks][3]);
            if (warp == 0) {
                float sc[4] = {0.f, 0.f, 0.f, 0.f};
#pragma unroll
                for (int i = 0; i < 4; i++) {
                    uint32_t b0, b1, b2, b3;
                    ldsm_x4(ab + 4096 + (lane & 7) * 256 + (4 * i + (lane >> 3)) * 16, b0, b1, b2, b3);
                    mma_16816(sc, qf[2 * i], b0, b1);
                    mma_16816(sc, qf[2 * i + 1], b2, b3);
                }
                const uint32_t mraw = *reinterpret_cast<const uint32_t*>(smem + kSmemAux + r * kAuxBytes + 8192 + lane * 4);
                const float mk0 = __uint_as_float(mraw << 16), mk1 = __uint_as_float(mraw & 0xffff0000u);
                const float bias0 = (1.0f - mk0) * (-1000000000.0f / kScale);
                const float bias1 = (1.0f - mk1) * (-1000000000.0f / kScale);
                sc[0] += bias0; sc[1] += bias1; sc[2] += bias0; sc[3] += bias1;
                m0 = quad_max(fmaxf(sc[0], sc[1]));
                m1 = quad_max(fmaxf(sc[2], sc[3]));
                const float p0 = ex2((sc[0] - m0) * kC2), p1 = ex2((sc[1] - m0) * kC2);
                const float p2 = ex2((sc[2] - m1) * kC2), p3 = ex2((sc[3] - m1) * kC2);
                l0 = p0 + p1; l1 = p2 + p3;
                const uint32_t pa0 = pack_bf16(p0, p1), pa1 = pack_bf16(p2, p3);
#pragma unroll
                for (int i = 0; i < 4; i++) {
                    uint32_t b0, b1, b2, b3;
                    ldsm_x4_t(ab + 6144 + (lane & 7) * 256 + (4 * i + (lane >> 3)) * 16, b0, b1, b2, b3);
                    mma_1688(o[4 * i + 0], pa0, pa1, b0);
                    mma_1688(o[4 * i + 1], pa0, pa1, b1);
                    mma_1688(o[4 * i + 2], pa0, pa1, b2);
                    mma_1688(o[4 * i + 3], pa0, pa1, b3);
                }
            }

            float st[kGrp][2][4];
            float mx0, mx1;
            auto scores = [&]() {
                mx0 = m0; mx1 = m1;
#pragma unroll
                for (int t = 0; t < kGrp; t++) {
#pragma unroll
                    for (int j = 0; j < 2; j++) { st[t][j][0] = 0.f; st[t][j][1] = 0.f; st[t][j][2] = 0.f; st[t][j][3] = 0.f; }
                    const uint32_t kb = sbase + kSmemRing + s * kTileBytes;
                    mbar_wait(bar_full + s * 8, ph);
#pragma unroll
                    for (int i = 0; i < 4; i++) {
#pragma unroll
                        for (int j = 0; j < 2; j++) {
                            uint32_t b0, b1, b2, b3;
                            ldsm_x4(kb + koff[i] + j * 1024, b0, b1, b2, b3);
                            mma_16816(st[t][j], qf[2 * i], b0, b1);
                            mma_16816(st[t][j], qf[2 * i + 1], b2, b3);
                        }
                    }
                    __syncwarp();
                    if (lane == 0) mbar_arrive(bar_empty + s * 8);
                    if (++s == kStages) { s = 0; ph ^= 1; }
                    mx0 = fmaxf(mx0, fmaxf(fmaxf(st[t][0][0], st[t][0][1]), fmaxf(st[t][1][0], st[t][1][1])));
                    mx1 = fmaxf(mx1, fmaxf(fmaxf(st[t][0][2], st[t][0][3]), fmaxf(st[t][1][2], st[t][1][3])));
                }
                mx0 = quad_max(mx0);
                mx1 = quad_max(mx1);
            };
            auto probs = [&](int t, float mb0, float mb1, uint32_t (&pa)[4]) {
                const float p00 = ex2(fmaf(st[t][0][0], kC2, -mb0)), p01 = ex2(fmaf(st[t][0][1], kC2, -mb0));
                const float p02 = ex2(fmaf(st[t][0][2], kC2, -mb1)), p03 = ex2(fmaf(st[t][0][3], kC2, -mb1));
                const float p10 = ex2(fmaf(st[t][1][0], kC2, -mb0)), p11 = ex2(fmaf(st[t][1][1], kC2, -mb0));
                const float p12 = ex2(fmaf(st[t][1][2], kC2, -mb1)), p13 = ex2(fmaf(st[t][1][3], kC2, -mb1));
                l0 += (p00 + p01) + (p10 + p11);
                l1 += (p02 + p03) + (p12 + p13);
                pa[0] = pack_bf16(p00, p01); pa[1] = pack_bf16(p02, p03);
                pa[2] = pack_bf16(p10, p11); pa[3] = pack_bf16(p12, p13);
            };

#pragma unroll 1
            for (int gi = 0; gi < kGroups - 1; gi++) {
                scores();
                const float al0 = ex2((m0 - mx0) * kC2), al1 = ex2((m1 - mx1) * kC2);
                m0 = mx0; m1 = mx1;
                l0 *= al0; l1 *= al1;
                uint32_t pa[kGrp][4];
#pragma unroll
                for (int t = 0; t < kGrp; t++) probs(t, mx0 * kC2, mx1 * kC2, pa[t]);
#pragma unroll
                for (int i = 0; i < 16; i++) { o[i][0] *= al0; o[i][1] *= al0; o[i][2] *= al1; o[i][3] *= al1; }
#pragma unroll
                for (int t = 0; t < kGrp; t++) {
                    const uint32_t vb = sbase + kSmemRing + s * kTileBytes;
                    mbar_wait(bar_full + s * 8, ph);
#pragma unroll
                    for (int i = 0; i < 8; i++) {
                        uint32_t b0, b1, b2, b3;
                        ldsm_x4_t(vb + voff[i], b0, b1, b2, b3);
                        mma_16816(o[2 * i], pa[t], b0, b1);
                        mma_16816(o[2 * i + 1], pa[t], b2, b3);
                    }
                    __syncwarp();
                    if (lane == 0) mbar_arrive(bar_empty + s * 8);
                    if (++s == kStages) { s = 0; ph ^= 1; }
                }
            }

            scores();
            if (tq == 0) { mbuf[warp * 16 + g] = mx0; mbuf[warp * 16 + g + 8] = mx1; }
            consumer_sync();
#pragma unroll
            for (int w = 0; w < kNCW; w++) {
                mx0 = fmaxf(mx0, mbuf[w * 16 + g]);
                mx1 = fmaxf(mx1, mbuf[w * 16 + g + 8]);
            }
            {
                const float f0 = ex2((m0 - mx0) * kC2), f1 = ex2((m1 - mx1) * kC2);
                l0 *= f0; l1 *= f1;
#pragma unroll
                for (int t = 0; t < kGrp; t++) {
                    uint32_t pa[4];
                    probs(t, mx0 * kC2, mx1 * kC2, pa);
                    sts128u(pbuf + (t * kNCW + warp) * 512, pa);
                }
                l0 = quad_sum(l0);
                l1 = quad_sum(l1);
                if (tq == 0) { lbuf[warp * 16 + g] = l0; lbuf[warp * 16 + g + 8] = l1; }
#pragma unroll
                for (int i = 0; i < 16; i++)
                    sts128(red + (warp * 16 + i) * 512, o[i][0] * f0, o[i][1] * f0, o[i][2] * f1, o[i][3] * f1);
            }
            consumer_sync();
            float oc[4][4];
            uint32_t pt[kGrp][kNCW][4];
#pragma unroll
            for (int i = 0; i < 4; i++) {
                lds128(red + (4 * warp + i) * 512, oc[i]);
#pragma unroll
                for (int w = 1; w < kNCW; w++) {
                    float v[4];
                    lds128(red + (w * 16 + 4 * warp + i) * 512, v);
                    oc[i][0] += v[0]; oc[i][1] += v[1]; oc[i][2] += v[2]; oc[i][3] += v[3];
                }
            }
#pragma unroll
            for (int t = 0; t < kGrp; t++)
#pragma unroll
                for (int w = 0; w < kNCW; w++) lds128u(pbuf + (t * kNCW + w) * 512, pt[t][w]);
            const float inv0 = rcp((lbuf[g] + lbuf[16 + g]) + (lbuf[32 + g] + lbuf[48 + g]));
            const float inv1 = rcp((lbuf[g + 8] + lbuf[16 + g + 8]) + (lbuf[32 + g + 8] + lbuf[48 + g + 8]));
#pragma unroll
            for (int t = 0; t < kGrp; t++) {
                const uint32_t vb = sbase + kSmemRing + s * kTileBytes;
                mbar_wait(bar_full + s * 8, ph);
#pragma unroll
                for (int w = 0; w < kNCW; w++) {
#pragma unroll
                    for (int i = 0; i < 2; i++) {
                        uint32_t b0, b1, b2, b3;
                        ldsm_x4_t(vb + voff2[i] + w * 2048, b0, b1, b2, b3);
                        mma_16816(oc[2 * i], pt[t][w], b0, b1);
                        mma_16816(oc[2 * i + 1], pt[t][w], b2, b3);
                    }
                }
                __syncwarp();
                if (lane == 0) mbar_arrive(bar_empty + s * 8);
                if (++s == kStages) { s = 0; ph ^= 1; }
            }
            {
                uint32_t w[2][4];
#pragma unroll
                for (int i = 0; i < 4; i++) {
                    w[0][i] = pack_bf16(oc[i][0] * inv0, oc[i][1] * inv0);
                    w[1][i] = pack_bf16(oc[i][2] * inv1, oc[i][3] * inv1);
                }
                const bool hi = tq & 2, od = tq & 1;
#pragma unroll
                for (int h = 0; h < 2; h++) {
                    uint32_t a = hi ? w[h][0] : w[h][2], b = hi ? w[h][1] : w[h][3];
                    a = __shfl_xor_sync(0xffffffffu, a, 2);
                    b = __shfl_xor_sync(0xffffffffu, b, 2);
                    if (hi) { w[h][0] = a; w[h][1] = b; } else { w[h][2] = a; w[h][3] = b; }
                }
#pragma unroll
                for (int h = 0; h < 2; h++) {
                    uint32_t a = od ? w[h][0] : w[h][1], b = od ? w[h][2] : w[h][3];
                    a = __shfl_xor_sync(0xffffffffu, a, 1);
                    b = __shfl_xor_sync(0xffffffffu, b, 1);
                    if (od) { w[h][0] = a; w[h][2] = b; } else { w[h][1] = a; w[h][3] = b; }
                }
                uint4* op = reinterpret_cast<uint4*>(out + ((size_t)head * 16 + g) * kD + 32 * warp) + tq;
                op[0] = make_uint4(w[0][0], w[0][1], w[0][2], w[0][3]);
                op[8 * kD / 8] = make_uint4(w[1][0], w[1][1], w[1][2], w[1][3]);
            }
        }
    }
}

typedef CUresult (*EncodeTiledFn)(CUtensorMap*, CUtensorMapDataType, cuuint32_t, void*, const cuuint64_t*, const cuuint64_t*,
                                  const cuuint32_t*, const cuuint32_t*, CUtensorMapInterleave, CUtensorMapSwizzle,
                                  CUtensorMapL2promotion, CUtensorMapFloatOOBfill);

void make_map(EncodeTiledFn enc, CUtensorMap* map, const void* ptr) {
    const cuuint64_t rows = (cuuint64_t)kHeads * kC;
    cuuint64_t dims[3] = {64, rows, 2};
    cuuint64_t strides[2] = {256, 128};
    cuuint32_t box[3] = {64, (cuuint32_t)kTile, 2};
    cuuint32_t estr[3] = {1, 1, 1};
    enc(map, CU_TENSOR_MAP_DATA_TYPE_BFLOAT16, 3, const_cast<void*>(ptr), dims, strides, box, estr,
        CU_TENSOR_MAP_INTERLEAVE_NONE, CU_TENSOR_MAP_SWIZZLE_128B, CU_TENSOR_MAP_L2_PROMOTION_L2_128B,
        CU_TENSOR_MAP_FLOAT_OOB_FILL_NONE);
}

}

extern "C" void kernel_launch(void* const* d_in, const int* in_sizes, int n_in, void* d_out, int out_size) {
    (void)in_sizes; (void)n_in; (void)out_size;
    static EncodeTiledFn enc = nullptr;
    if (!enc) {
        void* fn = nullptr;
        cudaDriverEntryPointQueryResult qres;
        cudaGetDriverEntryPoint("cuTensorMapEncodeTiled", &fn, cudaEnableDefault, &qres);
        enc = (EncodeTiledFn)fn;
        cudaFuncSetAttribute(tree_attn_kernel, cudaFuncAttributeMaxDynamicSharedMemorySize, kSmemTotal);
    }
    CUtensorMap map_k, map_v;
    make_map(enc, &map_k, d_in[1]);
    make_map(enc, &map_v, d_in[2]);
    tree_attn_kernel<<<kCtas, kThreads, kSmemTotal>>>(
        (const __nv_bfloat16*)d_in[1], (const __nv_bfloat16*)d_in[0], (const __nv_bfloat16*)d_in[3],
        (const __nv_bfloat16*)d_in[4], (const __nv_bfloat16*)d_in[5], (__nv_bfloat16*)d_out, map_k, map_v);
}
```
